```python
import torch

def _softmax(x, axis=-1):
    return torch.softmax(x, dim=axis)
def _gelu(x):
    return torch.nn.functional.gelu(x, approximate="tanh")
def _silu(x):
    return torch.nn.functional.silu(x)
def _sigmoid(x):
    return torch.sigmoid(x)
def _layernorm(x, axis=-1, eps=1e-5):
    m = x.mean(dim=axis, keepdim=True)
    v = x.var(dim=axis, keepdim=True, unbiased=False)
    return (x - m) / torch.sqrt(v + eps)
def _scatter_add(tgt, idx, src, axis=0):
    return tgt.clone().index_add_(axis, idx, src)
def _segment_sum(src, seg, n):
    out = torch.zeros((n,) + src.shape[1:], dtype=src.dtype)
    return out.index_add_(0, seg, src)
def _pad(x, pw):
    flat = tuple(v for pair in reversed(pw) for v in pair)
    return torch.nn.functional.pad(x, flat)

kernel_name = 'interleave_layers__spectral_gfnet__ssm_conv_s5__prompt'

def setup_inputs():

    _w = (lambda a: (lambda t: t.to(torch.bfloat16) if t.is_floating_point() else t)(torch.as_tensor(a)))
    def _A_setup():
        B, S, D = 1, 2048, 512
        Df = D // 2 + 1
        return {
            "x": _w((lambda *s: torch.randn(*s, dtype=torch.bfloat16) * 0.05)(B, S, D)),
            "w_r": _w((lambda *s: torch.randn(*s, dtype=torch.bfloat16) * 1.6)(S, Df) * 0.02),
            "w_i": _w((lambda *s: torch.randn(*s, dtype=torch.bfloat16) * 1.6)(S, Df) * 0.02),
        }
    _A_in = _A_setup()

    def _B_setup():
        B, S, D = 1, 2048, 512
        P = D
        Lambda_re = -0.5 * (lambda _x: torch.exp(torch.as_tensor(_x)))((lambda *s: torch.randn(*s, dtype=torch.bfloat16) * 0.2)(P))
        Lambda_im = (lambda *s: torch.randn(*s, dtype=torch.bfloat16) * 0.4)(P) * 1.0
        B_re = (lambda *s: torch.randn(*s, dtype=torch.bfloat16) * 0.2)(P, D) * (D ** -0.5)
        B_im = (lambda *s: torch.randn(*s, dtype=torch.bfloat16) * 0.2)(P, D) * (D ** -0.5)
        C_re = (lambda *s: torch.randn(*s, dtype=torch.bfloat16) * 0.2)(D, P) * (P ** -0.5)
        C_im = (lambda *s: torch.randn(*s, dtype=torch.bfloat16) * 0.2)(D, P) * (P ** -0.5)
        log_dt = (lambda *s: torch.randn(*s, dtype=torch.bfloat16) * 0.2)(P) * 0.3 - 2.0
        Dskip = (lambda *s: torch.randn(*s, dtype=torch.bfloat16) * 0.05)(D)
        return {
            "x": _w((lambda *s: torch.randn(*s, dtype=torch.bfloat16) * 0.05)(B, S, D)),
            "Lambda_re": _w(Lambda_re),
            "Lambda_im": _w(Lambda_im),
            "B_re": _w(B_re),
            "B_im": _w(B_im),
            "C_re": _w(C_re),
            "C_im": _w(C_im),
            "log_dt": _w(log_dt),
            "Dskip": _w(Dskip),
        }
    _B_in = _B_setup()

    return {
        "A_x": _A_in["x"],
        "A_w_r": _A_in["w_r"],
        "A_w_i": _A_in["w_i"],
        "B_x": _B_in["x"],
        "B_Lambda_re": _B_in["Lambda_re"],
        "B_Lambda_im": _B_in["Lambda_im"],
        "B_B_re": _B_in["B_re"],
        "B_B_im": _B_in["B_im"],
        "B_C_re": _B_in["C_re"],
        "B_C_im": _B_in["C_im"],
        "B_log_dt": _B_in["log_dt"],
        "B_Dskip": _B_in["Dskip"],
    }

def reference(A_x, A_w_r, A_w_i, B_x, B_Lambda_re, B_Lambda_im, B_B_re, B_B_im, B_C_re, B_C_im, B_log_dt, B_Dskip):
    def _A_ref(x, w_r, w_i):
        B, S, D = x.shape
        X = (lambda x, axes=(-2,-1): torch.fft.rfft2(x.float(), dim=axes))(x, axes=(-2, -1))
        W = w_r + 1j * w_i
        X = X * W
        y = (lambda x, s, axes=(-2,-1): torch.fft.irfft2(x, s=s, dim=axes).to(torch.bfloat16))(X, (S, D), axes=(-2, -1))
        return y

    def _B_ref(x, Lambda_re, Lambda_im, B_re, B_im, C_re, C_im, log_dt, Dskip):
        Bsz, L, H = x.shape
        Lam = Lambda_re + 1j * Lambda_im
        Bmat = B_re + 1j * B_im
        Cmat = C_re + 1j * C_im
        dt = torch.exp(log_dt)
        Lam_bar = torch.exp(dt * Lam)
        B_bar = ((Lam_bar - 1.0) / Lam)[:, None] * Bmat
        Bu = torch.einsum("bld,pd->blp", x + 0j, B_bar)
        h = torch.zeros_like(Bu[:, 0, :])
        hs = []
        for t in range(L):
            h = Lam_bar[None, :] * h + Bu[:, t, :]
            hs.append(h)
        hseq = torch.stack(hs, 1)
        y = 2.0 * torch.einsum("blp,dp->bld", hseq, Cmat).real + x * Dskip[None, None, :]
        return y

    x = A_x
    x = x + _A_ref(_layernorm(x, axis=-1), A_w_r, A_w_i)
    x = x + _B_ref(_layernorm(x, axis=-1), B_Lambda_re, B_Lambda_im, B_B_re, B_B_im, B_C_re, B_C_im, B_log_dt, B_Dskip)
    x = x + _A_ref(_layernorm(x, axis=-1), A_w_r, A_w_i)
    x = x + _B_ref(_layernorm(x, axis=-1), B_Lambda_re, B_Lambda_im, B_B_re, B_B_im, B_C_re, B_C_im, B_log_dt, B_Dskip)
    return x
```

```cpp
#include <cuda_runtime.h>
#include <cuda_bf16.h>
#include <stdint.h>

namespace tb {
constexpr double PI = 3.14159265358979323846264338327950288;
constexpr double ccos_small(double x) { double x2 = x * x, term = 1.0, s = 1.0; for (int i = 1; i < 14; i++) { term *= -x2 / ((2 * i - 1) * (2 * i)); s += term; } return s; }
constexpr double csin_small(double x) { double x2 = x * x, term = x, s = x; for (int i = 1; i < 14; i++) { term *= -x2 / ((2 * i) * (2 * i + 1)); s += term; } return s; }
constexpr double cos2pi(int i, int N) {
    i %= N; if (i < 0) i += N;
    if (i > N / 2) i = N - i;
    bool neg = false; if (i > N / 4) { i = N / 2 - i; neg = true; }
    double r = (i <= N / 8) ? ccos_small(2 * PI * i / N) : csin_small(2 * PI * (N / 4 - i) / N);
    return neg ? -r : r;
}
constexpr double sin2pi(int i, int N) { return cos2pi(i - N / 4, N); }
constexpr uint16_t to_bf16(double v) {
    if (v == 0.0) return 0;
    uint16_t sign = v < 0 ? 0x8000 : 0; if (v < 0) v = -v;
    int e = 0; while (v >= 2.0) { v *= 0.5; e++; } while (v < 1.0) { v *= 2.0; e--; }
    double m = (v - 1.0) * 128.0; int mi = (int)m; double fr = m - mi;
    if (fr > 0.5 || (fr == 0.5 && (mi & 1))) mi++;
    if (mi == 128) { mi = 0; e++; }
    return sign | (uint16_t)((e + 127) << 7) | (uint16_t)mi;
}
struct Cos512 { uint16_t v[512]; constexpr Cos512() : v() { for (int i = 0; i < 512; i++) v[i] = to_bf16(cos2pi(i, 512) / 16.0); } };
template <bool TRANS> struct QTab {
    uint16_t v[512 * 512];
    constexpr QTab() : v() {
        Cos512 c; uint16_t dc = to_bf16(0.044194173824159220275), ndc = dc | 0x8000;
        for (int k = 0; k < 512; k++) {
            int s = k >> 1; int off = (k & 1) ? 128 : 0;
            for (int d = 0; d < 512; d++) {
                uint16_t val = (k == 0) ? ((d & 1) ? ndc : dc) : (k == 1) ? dc : c.v[(s * d + off) & 511];
                int r = TRANS ? d : k, kk = TRANS ? k : d;
                v[((((r >> 7) * 8 + (kk >> 6)) * 8 + ((kk & 63) >> 3)) * 16 + ((r & 127) >> 3)) * 64 + (r & 7) * 8 + (kk & 7)] = val;
            }
        }
    }
};
struct FTab {
    uint16_t v[4096 + 8192 + 8192 + 4096];
    constexpr FTab() : v() {
        for (int m = 0; m < 64; m++) for (int kk = 0; kk < 64; kk++) {
            int f1 = (m >> 4) * 8 + (m & 7), c = (m >> 3) & 1;
            {
                int cp = kk >> 5, t1 = kk & 31;
                double co = cos2pi(t1 * f1, 32), si = sin2pi(t1 * f1, 32);
                double val = (c == 0) ? (cp == 0 ? co : si) : (cp == 0 ? -si : co);
                v[((kk >> 3) * 8 + (m >> 3)) * 64 + (m & 7) * 8 + (kk & 7)] = to_bf16(val);
            }
            {
                int fp = (kk >> 4) * 8 + (kk & 7), cp = (kk >> 3) & 1;
                double co = cos2pi(fp * f1, 32), si = sin2pi(fp * f1, 32);
                double val = (c == 0) ? (cp == 0 ? co : -si) : (cp == 0 ? si : co);
                v[4096 + 16384 + ((kk >> 3) * 8 + (m >> 3)) * 64 + (m & 7) * 8 + (kk & 7)] = to_bf16(val);
            }
        }
        for (int kk = 0; kk < 64; kk++) for (int n = 0; n < 128; n++) {
            int jj = n >> 3, q = (n >> 1) & 3, c = n & 1;
            {
                int f2 = 4 * jj + q;
                double val = c == 0 ? cos2pi(kk * f2, 64) : -sin2pi(kk * f2, 64);
                v[4096 + ((kk >> 3) * 16 + (n >> 3)) * 64 + (n & 7) * 8 + (kk & 7)] = to_bf16(val);
            }
            {
                int f2 = (kk & 56) + 4 * (kk & 1) + ((kk >> 1) & 3);
                int t2 = 8 * (jj >> 1) + 2 * q + (jj & 1);
                double val = c == 0 ? cos2pi(f2 * t2, 64) : sin2pi(f2 * t2, 64);
                v[4096 + 8192 + ((kk >> 3) * 16 + (n >> 3)) * 64 + (n & 7) * 8 + (kk & 7)] = to_bf16(val);
            }
        }
    }
};
}

__device__ __align__(1024) constexpr tb::QTab<false> g_T1 = tb::QTab<false>();
__device__ __align__(1024) constexpr tb::QTab<true> g_T2 = tb::QTab<true>();
__device__ __align__(1024) constexpr tb::FTab g_T3 = tb::FTab();

__device__ __align__(1024) float g_XF[512 * 2048];
__device__ __align__(1024) uint16_t g_XB[16 * 8 * 8192];
__device__ __align__(1024) uint16_t g_H[16 * 16 * 8192];
__device__ __align__(1024) uint16_t g_WB[8 * 8 * 8192];
__device__ __align__(1024) uint16_t g_WC1[4 * 16 * 8192];
__device__ __align__(1024) uint16_t g_WC2[4 * 16 * 8192];
__device__ __align__(1024) uint16_t g_WE1[4 * 8 * 8192];
__device__ __align__(1024) uint32_t g_WF[256 * 2048];
__device__ __align__(16) float g_SSQ[4 * 2048];
__device__ __align__(16) uint4 g_AGG[2 * 16 * 512];
__device__ unsigned g_HFLAG[2 * 16 * 16];
__device__ unsigned g_epoch;

__device__ __forceinline__ uint32_t smem_u32(const void* p) { return (uint32_t)__cvta_generic_to_shared(p); }
__device__ __forceinline__ uint64_t mkdesc(uint32_t addr, uint32_t lbo, uint32_t sbo) {
    return (uint64_t)((addr & 0x3FFFF) >> 4) | ((uint64_t)(lbo >> 4) << 16) | ((uint64_t)(sbo >> 4) << 32);
}
__device__ __forceinline__ void mbar_init(uint32_t a, int c) { asm volatile("mbarrier.init.shared::cta.b64 [%0], %1;" ::"r"(a), "r"(c)); }
__device__ __forceinline__ void mbar_expect(uint32_t a, int bytes) { asm volatile("mbarrier.arrive.expect_tx.shared::cta.b64 _, [%0], %1;" ::"r"(a), "r"(bytes) : "memory"); }
__device__ __forceinline__ void mbar_arrive(uint32_t a) { asm volatile("mbarrier.arrive.shared::cta.b64 _, [%0];" ::"r"(a) : "memory"); }
__device__ __forceinline__ void mbar_arrive_remote(uint32_t ra) { asm volatile("mbarrier.arrive.release.cluster.shared::cluster.b64 _, [%0];" ::"r"(ra) : "memory"); }
__device__ __forceinline__ bool mbar_try(uint32_t a, int ph) {
    uint32_t ok;
    asm volatile("{\n.reg .pred p;\nmbarrier.try_wait.parity.shared::cta.b64 p, [%1], %2;\nselp.u32 %0, 1, 0, p;\n}" : "=r"(ok) : "r"(a), "r"(ph) : "memory");
    return ok;
}
__device__ __forceinline__ bool mbar_try_cluster(uint32_t a, int ph) {
    uint32_t ok;
    asm volatile("{\n.reg .pred p;\nmbarrier.try_wait.parity.acquire.cluster.shared::cta.b64 p, [%1], %2;\nselp.u32 %0, 1, 0, p;\n}" : "=r"(ok) : "r"(a), "r"(ph) : "memory");
    return ok;
}
__device__ __forceinline__ void mbar_wait(uint32_t a, int ph) {
    int n = 0;
    while (!mbar_try(a, ph)) { if (++n > (1 << 22)) __trap(); }
}
__device__ __forceinline__ void mbar_wait_cluster(uint32_t a, int ph) {
    int n = 0;
    while (!mbar_try_cluster(a, ph)) { if (++n > (1 << 22)) __trap(); }
}
__device__ __forceinline__ void bulk_g2s(uint32_t dst, const void* src, int bytes, uint32_t bar) {
    asm volatile("cp.async.bulk.shared::cluster.global.mbarrier::complete_tx::bytes [%0], [%1], %2, [%3];" ::"r"(dst), "l"(src), "r"(bytes), "r"(bar) : "memory");
}
__device__ __forceinline__ void cp_async16(uint32_t dst, const void* src) { asm volatile("cp.async.cg.shared.global [%0], [%1], 16;" ::"r"(dst), "l"(src) : "memory"); }
__device__ __forceinline__ void cp_commit() { asm volatile("cp.async.commit_group;" ::: "memory"); }
template <int N> __device__ __forceinline__ void cp_wait() { asm volatile("cp.async.wait_group %0;" ::"n"(N) : "memory"); }
__device__ __forceinline__ void fence_async_smem() { asm volatile("fence.proxy.async.shared::cta;" ::: "memory"); }
__device__ __forceinline__ void fence_async_all() { asm volatile("fence.proxy.async;" ::: "memory"); }
__device__ __forceinline__ void bar_sync(int id, int n) { asm volatile("bar.sync %0, %1;" ::"r"(id), "r"(n) : "memory"); }
__device__ __forceinline__ void wg_fence() { asm volatile("wgmma.fence.sync.aligned;" ::: "memory"); }
__device__ __forceinline__ void wg_commit() { asm volatile("wgmma.commit_group.sync.aligned;" ::: "memory"); }
template <int N> __device__ __forceinline__ void wg_wait() { asm volatile("wgmma.wait_group.sync.aligned %0;" ::"n"(N) : "memory"); }
template <int N> __device__ __forceinline__ void reg_fence(float (&d)[N]) {
#pragma unroll
    for (int i = 0; i < N; i++) asm volatile("" : "+f"(d[i])::"memory");
}
__device__ __forceinline__ uint32_t pack_bf16(float lo, float hi) {
    uint32_t r; asm("cvt.rn.bf16x2.f32 %0, %1, %2;" : "=r"(r) : "f"(hi), "f"(lo)); return r;
}
__device__ __forceinline__ float bf_lo(uint32_t u) { return __uint_as_float(u << 16); }
__device__ __forceinline__ float bf_hi(uint32_t u) { return __uint_as_float(u & 0xffff0000u); }

#define ACC8(d, o) "+f"(d[o + 0]), "+f"(d[o + 1]), "+f"(d[o + 2]), "+f"(d[o + 3]), "+f"(d[o + 4]), "+f"(d[o + 5]), "+f"(d[o + 6]), "+f"(d[o + 7])
#define ACC32(d) ACC8(d, 0), ACC8(d, 8), ACC8(d, 16), ACC8(d, 24)
#define ACC64(d) ACC32(d), ACC8(d, 32), ACC8(d, 40), ACC8(d, 48), ACC8(d, 56)
#define R32 "{%0,%1,%2,%3,%4,%5,%6,%7,%8,%9,%10,%11,%12,%13,%14,%15,%16,%17,%18,%19,%20,%21,%22,%23,%24,%25,%26,%27,%28,%29,%30,%31}"
#define R64 "{%0,%1,%2,%3,%4,%5,%6,%7,%8,%9,%10,%11,%12,%13,%14,%15,%16,%17,%18,%19,%20,%21,%22,%23,%24,%25,%26,%27,%28,%29,%30,%31,%32,%33,%34,%35,%36,%37,%38,%39,%40,%41,%42,%43,%44,%45,%46,%47,%48,%49,%50,%51,%52,%53,%54,%55,%56,%57,%58,%59,%60,%61,%62,%63}"

template <int TB> __device__ __forceinline__ void mma128_ss(float (&d)[64], uint64_t da, uint64_t db, int acc) {
    asm volatile("{\n.reg .pred p;\nsetp.ne.b32 p, %66, 0;\n"
                 "wgmma.mma_async.sync.aligned.m64n128k16.f32.bf16.bf16 " R64 ", %64, %65, p, 1, 1, 0, %67;\n}\n"
                 : ACC64(d) : "l"(da), "l"(db), "r"(acc), "n"(TB));
}
template <int TB> __device__ __forceinline__ void mma64_ss(float (&d)[32], uint64_t da, uint64_t db, int acc) {
    asm volatile("{\n.reg .pred p;\nsetp.ne.b32 p, %34, 0;\n"
                 "wgmma.mma_async.sync.aligned.m64n64k16.f32.bf16.bf16 " R32 ", %32, %33, p, 1, 1, 0, %35;\n}\n"
                 : ACC32(d) : "l"(da), "l"(db), "r"(acc), "n"(TB));
}
__device__ __forceinline__ void mma128_rs(float (&d)[64], uint32_t a0, uint32_t a1, uint32_t a2, uint32_t a3, uint64_t db, int acc) {
    asm volatile("{\n.reg .pred p;\nsetp.ne.b32 p, %69, 0;\n"
                 "wgmma.mma_async.sync.aligned.m64n128k16.f32.bf16.bf16 " R64 ", {%64,%65,%66,%67}, %68, p, 1, 1, 0;\n}\n"
                 : ACC64(d) : "r"(a0), "r"(a1), "r"(a2), "r"(a3), "l"(db), "r"(acc));
}

constexpr int KW_STAGES = 4;
constexpr int KW_SMEM = KW_STAGES * 32768;
__global__ void __launch_bounds__(256, 1) kw_kernel(const uint16_t* __restrict__ Bre, const uint16_t* __restrict__ Bim,
                                                    const uint16_t* __restrict__ Cre, const uint16_t* __restrict__ Cim,
                                                    const uint16_t* __restrict__ Dsk) {
    extern __shared__ __align__(1024) unsigned char sm[];
    const int tid = threadIdx.x, job = blockIdx.x;
    if (job >= 80) {
        for (int u = (job - 80) * 256 + tid; u < 65536; u += 16 * 256) {
            int mr = u & 7, m8 = (u >> 3) & 15, p8 = (u >> 7) & 7, pc = (u >> 10) & 15, dt = u >> 14;
            int d = dt * 128 + m8 * 8 + mr, c = p8 & 1, ch8 = pc * 4 + (p8 >> 1);
            uint4 v = *reinterpret_cast<const uint4*>((c ? Cim : Cre) + d * 512 + ch8 * 8);
            __nv_bfloat162 s = __float2bfloat162_rn(c ? -2.f : 2.f);
            __nv_bfloat162* p = reinterpret_cast<__nv_bfloat162*>(&v);
#pragma unroll
            for (int i = 0; i < 4; i++) p[i] = __hmul2(p[i], s);
            reinterpret_cast<uint4*>(g_WC2)[u] = v;
        }
        return;
    }
    const int type = job < 32 ? 0 : (job < 64 ? 1 : 2);
    int ta, tbi;
    if (type == 0) { ta = job >> 2; tbi = job & 3; }
    else if (type == 1) { ta = (job - 32) >> 3; tbi = (job - 32) & 7; }
    else { ta = (job - 64) >> 2; tbi = (job - 64) & 3; }
    const uint32_t sbase = smem_u32(sm);
    const uint16_t* T1 = g_T1.v;
    auto load = [&](int dc) {
        uint32_t sa = sbase + (dc % KW_STAGES) * 32768, sb = sa + 16384;
#pragma unroll
        for (int i = 0; i < 4; i++) {
            int u = i * 256 + tid;
            int r7 = u & 7, x8 = (u >> 3) & 15, d8 = u >> 7;
            if (type == 0) {
                int m = x8 * 8 + r7; int ch = ta * 64 + (m >> 4) * 8 + (m & 7), c = (m >> 3) & 1;
                cp_async16(sa + u * 16, (c ? Bim : Bre) + ch * 512 + dc * 64 + d8 * 8);
            } else {
                cp_async16(sa + u * 16, T1 + (ta * 8 + dc) * 8192 + u * 8);
            }
            if (type == 0) {
                cp_async16(sb + u * 16, T1 + (tbi * 8 + dc) * 8192 + u * 8);
            } else if (type == 1) {
                int d = dc * 64 + d8 * 8 + r7; int ch8 = tbi * 8 + (x8 >> 1), c = x8 & 1;
                cp_async16(sb + u * 16, (c ? Cim : Cre) + d * 512 + ch8 * 8);
            } else {
                uint4 v = *reinterpret_cast<const uint4*>(T1 + (tbi * 8 + dc) * 8192 + u * 8);
                uint4 s = *reinterpret_cast<const uint4*>(Dsk + dc * 64 + d8 * 8);
                __nv_bfloat162* p = reinterpret_cast<__nv_bfloat162*>(&v);
                const __nv_bfloat162* ps = reinterpret_cast<const __nv_bfloat162*>(&s);
#pragma unroll
                for (int k = 0; k < 4; k++) p[k] = __hmul2(p[k], ps[k]);
                *reinterpret_cast<uint4*>(sm + (dc % KW_STAGES) * 32768 + 16384 + u * 16) = v;
            }
        }
        cp_commit();
    };
    const int w = tid >> 7, ww = (tid >> 5) & 3, lane = tid & 31, g = lane >> 2, q = lane & 3;
    float acc[64];
#pragma unroll
    for (int i = 0; i < 64; i++) acc[i] = 0.f;
    load(0); load(1); load(2);
#pragma unroll 1
    for (int dc = 0; dc < 8; dc++) {
        if (dc < 6) cp_wait<2>(); else if (dc == 6) cp_wait<1>(); else cp_wait<0>();
        fence_async_smem();
        __syncthreads();
        uint32_t sa = sbase + (dc % KW_STAGES) * 32768, sb = sa + 16384;
        wg_fence();
#pragma unroll
        for (int kk = 0; kk < 4; kk++) {
            uint64_t da = mkdesc(sa + w * 1024 + kk * 4096, 2048, 128), db = mkdesc(sb + kk * 4096, 2048, 128);
            if (type == 1) mma128_ss<1>(acc, da, db, 1); else mma128_ss<0>(acc, da, db, 1);
        }
        wg_commit();
        if (dc + 3 < 8) load(dc + 3);
        wg_wait<0>();
    }
    reg_fence(acc);
    uint32_t* out; int nchunk;
    if (type == 0) { out = reinterpret_cast<uint32_t*>(g_WB); nchunk = 8; }
    else if (type == 1) { out = reinterpret_cast<uint32_t*>(g_WC1); nchunk = 16; }
    else { out = reinterpret_cast<uint32_t*>(g_WE1); nchunk = 8; }
#pragma unroll
    for (int j = 0; j < 16; j++) {
#pragma unroll
        for (int h = 0; h < 2; h++) {
            float v0 = acc[4 * j + 2 * h], v1 = acc[4 * j + 2 * h + 1];
            if (type == 1) { float s = (j & 1) ? -2.f : 2.f; v0 *= s; v1 *= s; }
            else if (tbi == 0 && j == 0 && q == 0) v1 = 0.f;
            int m8 = w * 8 + ww * 2 + h;
            out[((ta * nchunk + 2 * tbi + (j >> 3)) * 8 + (j & 7)) * 512 + m8 * 32 + g * 4 + q] = pack_bf16(v0, v1);
        }
    }
}

template <bool ADD_OLD>
__device__ __forceinline__ void finalize_freq(float (&v)[32], int kt, int tt, int hf, float* sred  , int tid) {
    const int w = tid >> 7, ww = (tid >> 5) & 3, lane = tid & 31, g = lane >> 2, q = lane & 3;
    const int k0 = kt * 128 + w * 64 + ww * 16 + g;
    const int t0 = tt * 128 + q * 32 + hf * 16;
#pragma unroll
    for (int h = 0; h < 2; h++) {
        float4* p = reinterpret_cast<float4*>(g_XF + (size_t)(k0 + 8 * h) * 2048 + t0);
        if (ADD_OLD) {
#pragma unroll
            for (int i = 0; i < 4; i++) {
                float4 o = p[i];
                v[16 * h + 4 * i] += o.x; v[16 * h + 4 * i + 1] += o.y; v[16 * h + 4 * i + 2] += o.z; v[16 * h + 4 * i + 3] += o.w;
            }
        }
#pragma unroll
        for (int i = 0; i < 4; i++) p[i] = make_float4(v[16 * h + 4 * i], v[16 * h + 4 * i + 1], v[16 * h + 4 * i + 2], v[16 * h + 4 * i + 3]);
    }
    float s[16];
    const float m0 = (k0 == 1) ? 0.f : 1.f;
#pragma unroll
    for (int i = 0; i < 16; i++) s[i] = m0 * v[i] * v[i] + v[16 + i] * v[16 + i];
#pragma unroll
    for (int i = 0; i < 8; i++) {
        bool up = lane & 16;
        float send = up ? s[i] : s[i + 8], keep = up ? s[i + 8] : s[i];
        s[i] = keep + __shfl_xor_sync(0xffffffffu, send, 16);
    }
#pragma unroll
    for (int i = 0; i < 4; i++) {
        bool up = lane & 8;
        float send = up ? s[i] : s[i + 4], keep = up ? s[i + 4] : s[i];
        s[i] = keep + __shfl_xor_sync(0xffffffffu, send, 8);
    }
#pragma unroll
    for (int i = 0; i < 2; i++) {
        bool up = lane & 4;
        float send = up ? s[i] : s[i + 2], keep = up ? s[i + 2] : s[i];
        s[i] = keep + __shfl_xor_sync(0xffffffffu, send, 4);
    }
    const int to = ((lane >> 4) & 1) * 8 + ((lane >> 3) & 1) * 4 + ((lane >> 2) & 1) * 2;
    *reinterpret_cast<float2*>(sred + (tid >> 5) * 64 + q * 16 + to) = make_float2(s[0], s[1]);
    bar_sync(1, 256);
    if (tid < 64) {
        float a = 0.f;
#pragma unroll
        for (int i = 0; i < 8; i++) a += sred[i * 64 + tid];
        g_SSQ[kt * 2048 + tt * 128 + (tid >> 4) * 32 + hf * 16 + (tid & 15)] = a;
    }
}

constexpr int K0_SMEM = 131072 + 65536 + 2048 + 64;
__global__ void __launch_bounds__(256, 1) k0_kernel(const uint16_t* __restrict__ x, const uint16_t* __restrict__ wr, const uint16_t* __restrict__ wi) {
    extern __shared__ __align__(1024) unsigned char sm[];
    const int tid = threadIdx.x, b = blockIdx.x;
    const int tt = b >> 3, kt = (b >> 1) & 3, hf = b & 1;
    const uint32_t sA = smem_u32(sm), sB = sA + 131072;
    float* sred = reinterpret_cast<float*>(sm + 131072 + 65536);
    const uint32_t bars = sB + 65536 + 2048;
    if (tid == 0) {
        for (int i = 0; i < 8; i++) mbar_init(bars + 8 * i, 1);
        asm volatile("fence.mbarrier_init.release.cluster;" ::: "memory");
        for (int i = 0; i < 8; i++) {
            mbar_expect(bars + 8 * i, 16384);
            bulk_g2s(sA + i * 16384, g_T1.v + (kt * 8 + i) * 8192, 16384, bars + 8 * i);
        }
        if (b == 0) g_epoch = g_epoch + 1;
    }
#pragma unroll
    for (int i = 0; i < 16; i++) {
        int u = i * 256 + tid;
        int nr = u & 7, d8l = (u >> 3) & 3, n8 = (u >> 5) & 7, d8h = u >> 8;
        int d8 = d8h * 4 + d8l;
        int t = tt * 128 + (nr >> 1) * 32 + hf * 16 + n8 * 2 + (nr & 1);
        cp_async16(sB + (d8 * 8 + n8) * 128 + nr * 16, x + t * 512 + d8 * 8);
    }
    cp_commit();
    {
        const int col = tid == 0 ? 256 : tid;
        uint32_t o[16];
#pragma unroll
        for (int jj = 0; jj < 16; jj++) {
            int f = b + 128 * jj;
            o[jj] = (uint32_t)wr[f * 257 + col] | ((uint32_t)wi[f * 257 + col] << 16);
        }
        int ti = ((b >> 3) & 3) * 32 + (b & 7) * 4 + (b >> 5);
        uint4* p = reinterpret_cast<uint4*>(g_WF + tid * 2048 + ti * 16);
#pragma unroll
        for (int i = 0; i < 4; i++) p[i] = make_uint4(o[4 * i], o[4 * i + 1], o[4 * i + 2], o[4 * i + 3]);
    }
    cp_wait<0>();
    fence_async_smem();
    __syncthreads();
    const int w = tid >> 7;
    float acc[32];
#pragma unroll
    for (int i = 0; i < 32; i++) acc[i] = 0.f;
#pragma unroll 1
    for (int dc = 0; dc < 8; dc++) {
        mbar_wait(bars + 8 * dc, 0);
        wg_fence();
#pragma unroll
        for (int kk = 0; kk < 4; kk++) {
            uint64_t da = mkdesc(sA + dc * 16384 + w * 1024 + kk * 4096, 2048, 128);
            uint64_t db = mkdesc(sB + dc * 8192 + kk * 2048, 1024, 128);
            mma64_ss<0>(acc, da, db, 1);
        }
        wg_commit();
    }
    wg_wait<0>();
    reg_fence(acc);
    float v[32];
#pragma unroll
    for (int j = 0; j < 8; j++) {
        v[2 * j] = acc[4 * j]; v[2 * j + 1] = acc[4 * j + 1];
        v[16 + 2 * j] = acc[4 * j + 2]; v[16 + 2 * j + 1] = acc[4 * j + 3];
    }
    finalize_freq<false>(v, kt, tt, hf, sred, tid);
}

constexpr int KC_SMEM = 49152 + 32768 + 64;
__global__ void __launch_bounds__(256, 1) kc_kernel() {
    extern __shared__ __align__(1024) unsigned char sm[];
    const int tid = threadIdx.x, b = blockIdx.x;
    const int w = tid >> 7, ww = (tid >> 5) & 3, lane = tid & 31, g = lane >> 2, q = lane & 3;
    const uint32_t sT = smem_u32(sm), sD = sT + 49152 + w * 16384, sD4 = sD + 8192, bar = sT + 49152 + 32768;
    const int slot = 2 * b + w;
    if (tid == 0) {
        mbar_init(bar, 1);
        asm volatile("fence.mbarrier_init.release.cluster;" ::: "memory");
        mbar_expect(bar, 49152);
        bulk_g2s(sT, g_T3.v, 49152, bar);
    }
    const int t1 = ww * 8 + g;
    float2 xr[8], xi[8], rs[8];
    float* pr = g_XF + (size_t)(2 * slot) * 2048 + t1 * 64 + 2 * q;
    {
#pragma unroll
        for (int j = 0; j < 8; j++) { xr[j] = *reinterpret_cast<const float2*>(pr + 8 * j); xi[j] = *reinterpret_cast<const float2*>(pr + 2048 + 8 * j); }
        const float* ps = g_SSQ + t1 * 64 + 2 * q;
#pragma unroll
        for (int j = 0; j < 8; j++) {
            float2 a = *reinterpret_cast<const float2*>(ps + 8 * j), c = *reinterpret_cast<const float2*>(ps + 2048 + 8 * j);
            float2 d = *reinterpret_cast<const float2*>(ps + 4096 + 8 * j), e = *reinterpret_cast<const float2*>(ps + 6144 + 8 * j);
            rs[j].x = rsqrtf(((a.x + c.x) + (d.x + e.x)) * (1.f / 512.f) + 1e-5f);
            rs[j].y = rsqrtf(((a.y + c.y) + (d.y + e.y)) * (1.f / 512.f) + 1e-5f);
        }
    }
    uint32_t wf[16];
    {
        const uint4* p = reinterpret_cast<const uint4*>(g_WF + slot * 2048 + (tid & 127) * 16);
#pragma unroll
        for (int i = 0; i < 4; i++) { uint4 v = p[i]; wf[4 * i] = v.x; wf[4 * i + 1] = v.y; wf[4 * i + 2] = v.z; wf[4 * i + 3] = v.w; }
    }
    float twc[16], tws[16];
#pragma unroll
    for (int i = 0; i < 16; i++) {
        int t2 = 8 * (i >> 1) + 2 * q + (i & 1);
        int idx = t1 * t2;
        if (idx >= 1024) idx -= 2048;
        float a = (float)idx * (-6.283185307179586f / 2048.f);
        __sincosf(a, &tws[i], &twc[i]);
    }
    {
        const float zi = slot == 0 ? 0.f : 1.f;
#pragma unroll
        for (int j = 0; j < 8; j++) {
            uint32_t a = pack_bf16(xr[j].x * rs[j].x, xr[j].y * rs[j].y);
            uint32_t c = pack_bf16(xi[j].x * rs[j].x * zi, xi[j].y * rs[j].y * zi);
            asm volatile("st.shared.u32 [%0], %1;" ::"r"(sD + (ww * 8 + j) * 128 + g * 16 + q * 4), "r"(a) : "memory");
            asm volatile("st.shared.u32 [%0], %1;" ::"r"(sD + ((4 + ww) * 8 + j) * 128 + g * 16 + q * 4), "r"(c) : "memory");
        }
    }
    fence_async_smem();
    __syncthreads();
    mbar_wait(bar, 0);
    uint32_t af[16];
    {
        float d1[32];
#pragma unroll
        for (int i = 0; i < 32; i++) d1[i] = 0.f;
        wg_fence();
#pragma unroll
        for (int kk = 0; kk < 4; kk++) mma64_ss<1>(d1, mkdesc(sT + kk * 2048, 1024, 128), mkdesc(sD + kk * 2048, 1024, 128), 1);
        wg_commit();
        wg_wait<0>();
        reg_fence(d1);
#pragma unroll
        for (int j = 0; j < 8; j++) {
            float r0 = d1[4 * j], r1 = d1[4 * j + 1], i0 = d1[4 * j + 2], i1 = d1[4 * j + 3];
            float c0 = twc[2 * j], s0 = tws[2 * j], c1 = twc[2 * j + 1], s1 = tws[2 * j + 1];
            af[2 * j] = pack_bf16(r0 * c0 - i0 * s0, r1 * c1 - i1 * s1);
            af[2 * j + 1] = pack_bf16(r0 * s0 + i0 * c0, r1 * s1 + i1 * c1);
        }
    }
    float acc[64];
#pragma unroll
    for (int i = 0; i < 64; i++) acc[i] = 0.f;
    wg_fence();
#pragma unroll
    for (int kb = 0; kb < 4; kb++) mma128_rs(acc, af[4 * kb], af[4 * kb + 1], af[4 * kb + 2], af[4 * kb + 3], mkdesc(sT + 8192 + kb * 4096, 2048, 128), kb);
    wg_commit();
    wg_wait<0>();
    reg_fence(acc);
    {
        float yr[16], yi[16];
#pragma unroll
        for (int jj = 0; jj < 16; jj++) {
            float r = acc[4 * jj] - acc[4 * jj + 3], i = acc[4 * jj + 1] + acc[4 * jj + 2];
            float a = bf_lo(wf[jj]) * (1.f / 2048.f), c = bf_hi(wf[jj]) * (1.f / 2048.f);
            yr[jj] = r * a - i * c; yi[jj] = r * c + i * a;
        }
#pragma unroll
        for (int kb = 0; kb < 4; kb++) {
            af[4 * kb] = pack_bf16(yr[4 * kb], yr[4 * kb + 1]);
            af[4 * kb + 1] = pack_bf16(yi[4 * kb], yi[4 * kb + 1]);
            af[4 * kb + 2] = pack_bf16(yr[4 * kb + 2], yr[4 * kb + 3]);
            af[4 * kb + 3] = pack_bf16(yi[4 * kb + 2], yi[4 * kb + 3]);
        }
    }
    wg_fence();
#pragma unroll
    for (int kb = 0; kb < 4; kb++) mma128_rs(acc, af[4 * kb], af[4 * kb + 1], af[4 * kb + 2], af[4 * kb + 3], mkdesc(sT + 24576 + kb * 4096, 2048, 128), kb);
    wg_commit();
    wg_wait<0>();
    reg_fence(acc);
#pragma unroll
    for (int j = 0; j < 8; j++) {
        float r0 = acc[8 * j] - acc[8 * j + 3], i0 = acc[8 * j + 1] + acc[8 * j + 2];
        float r1 = acc[8 * j + 4] - acc[8 * j + 7], i1 = acc[8 * j + 5] + acc[8 * j + 6];
        float c0 = twc[2 * j], s0 = tws[2 * j], c1 = twc[2 * j + 1], s1 = tws[2 * j + 1];
        uint32_t a = pack_bf16(r0 * c0 + i0 * s0, r1 * c1 + i1 * s1);
        uint32_t c = pack_bf16(i0 * c0 - r0 * s0, i1 * c1 - r1 * s1);
        asm volatile("st.shared.u32 [%0], %1;" ::"r"(sD4 + ((2 * ww) * 8 + j) * 128 + g * 16 + q * 4), "r"(a) : "memory");
        asm volatile("st.shared.u32 [%0], %1;" ::"r"(sD4 + ((2 * ww + 1) * 8 + j) * 128 + g * 16 + q * 4), "r"(c) : "memory");
    }
    fence_async_smem();
    bar_sync(2 + w, 128);
    {
        float d4[32];
#pragma unroll
        for (int i = 0; i < 32; i++) d4[i] = 0.f;
        wg_fence();
#pragma unroll
        for (int kk = 0; kk < 4; kk++) mma64_ss<1>(d4, mkdesc(sT + 40960 + kk * 2048, 1024, 128), mkdesc(sD4 + kk * 2048, 1024, 128), 1);
        wg_commit();
        wg_wait<0>();
        reg_fence(d4);
        const float zi = slot == 0 ? 0.f : 1.f;
#pragma unroll
        for (int j = 0; j < 8; j++) {
            xr[j].x += d4[4 * j]; xr[j].y += d4[4 * j + 1];
            xi[j].x += zi * d4[4 * j + 2]; xi[j].y += zi * d4[4 * j + 3];
            *reinterpret_cast<float2*>(pr + 8 * j) = xr[j];
            *reinterpret_cast<float2*>(pr + 2048 + 8 * j) = xi[j];
        }
    }
    {
        const bool odd = g & 1;
        const int tt = 4 * ww + (g >> 1);
#pragma unroll
        for (int c = 0; c < 2; c++) {
            uint32_t p[8];
#pragma unroll
            for (int j = 0; j < 8; j++) p[j] = c ? pack_bf16(xi[j].x, xi[j].y) : pack_bf16(xr[j].x, xr[j].y);
            const int k = 2 * slot + c;
            uint16_t* base = g_XB + (size_t)(tt * 8 + (k >> 6)) * 8192 + ((k >> 3) & 7) * 1024 + (k & 7) * 8;
#pragma unroll
            for (int l = 0; l < 2; l++) {
                uint32_t k0 = odd ? p[2 + l] : p[l], k1 = odd ? p[6 + l] : p[4 + l];
                uint32_t s0 = odd ? p[l] : p[2 + l], s1 = odd ? p[4 + l] : p[6 + l];
                uint32_t r0 = __shfl_xor_sync(0xffffffffu, s0, 4), r1 = __shfl_xor_sync(0xffffffffu, s1, 4);
                uint4 v = odd ? make_uint4(r0, r1, k0, k1) : make_uint4(k0, k1, r0, r1);
                int n8 = 4 * ((odd ? 2 : 0) + l) + q;
                *reinterpret_cast<uint4*>(base + n8 * 64) = v;
            }
        }
    }
}

constexpr int KS_MISC = 13 * 16384;
constexpr int KS_SMEM = KS_MISC + 512 + 512 + 2048;
__device__ __forceinline__ float2 cmul(float2 a, float2 b) { return make_float2(a.x * b.x - a.y * b.y, a.x * b.y + a.y * b.x); }
__device__ __forceinline__ float2 cfma(float2 a, float2 b, float2 c) { return make_float2(fmaf(a.x, b.x, fmaf(-a.y, b.y, c.x)), fmaf(a.x, b.y, fmaf(a.y, b.x, c.y))); }

template <int LAYER>
__global__ void __cluster_dims__(2, 1, 1) __launch_bounds__(384, 1)
ks_kernel(const __nv_bfloat16* __restrict__ Lre, const __nv_bfloat16* __restrict__ Lim, const __nv_bfloat16* __restrict__ logdt,
          const __nv_bfloat16* __restrict__ Dsk, float* __restrict__ out) {
    extern __shared__ __align__(1024) unsigned char sm[];
    const int tid = threadIdx.x, b = blockIdx.x;
    const int tt = b >> 3, pt = b & 7, kt = pt >> 1, hf = pt & 1;
    const uint32_t sb = smem_u32(sm);
    const uint32_t FULL = sb + KS_MISC, EMPTY = FULL + 13 * 8, SDONE = EMPTY + 13 * 8, RSBAR = SDONE + 64, PRDY = RSBAR + 8, PDAT = PRDY + 8;
    float* s_rs = reinterpret_cast<float*>(sm + KS_MISC + 512);
    float* sred = reinterpret_cast<float*>(sm + KS_MISC + 1024);
    if (tid == 0) {
        for (int i = 0; i < 13; i++) { mbar_init(FULL + 8 * i, 1); mbar_init(EMPTY + 8 * i, 2); }
        for (int i = 0; i < 8; i++) mbar_init(SDONE + 8 * i, 2);
        mbar_init(RSBAR, 2); mbar_init(PRDY, 256); mbar_init(PDAT, 256);
        asm volatile("fence.mbarrier_init.release.cluster;" ::: "memory");
    }
    const unsigned epoch = *reinterpret_cast<volatile unsigned*>(&g_epoch);
    __syncthreads();
    asm volatile("barrier.cluster.arrive.release.aligned;\nbarrier.cluster.wait.acquire.aligned;" ::: "memory");

    if (tid >= 256) {
        asm volatile("setmaxnreg.dec.sync.aligned.u32 72;");
        const int aw = (tid >> 5) - 8, lane = tid & 31;
        if (aw == 0) {
            if (lane == 0) {
                const uint16_t* WE = LAYER == 0 ? g_WE1 : g_T2.v;
                const uint16_t* WC = LAYER == 0 ? g_WC1 : g_WC2;
                auto ld = [&](int slot, int use, const uint16_t* src) {
                    if (use > 0) mbar_wait(EMPTY + 8 * slot, (use - 1) & 1);
                    mbar_expect(FULL + 8 * slot, 16384);
                    bulk_g2s(sb + slot * 16384, src, 16384, FULL + 8 * slot);
                };
                auto kc = [&](int s) { return (4 * (1 - hf) + s) & 7; };
                const uint16_t* X = g_XB + (size_t)tt * 8 * 8192;
                const uint16_t* WB = g_WB + (size_t)pt * 8 * 8192;
                for (int s = 0; s < 5; s++) { ld(8 + s, 0, X + kc(s) * 8192); ld(s, 0, WB + kc(s) * 8192); }
                for (int s = 5; s < 8; s++) ld(s, 0, WB + kc(s) * 8192);
                for (int s = 5; s < 8; s++) { mbar_wait(SDONE + 8 * (s - 5), 0); ld(3 + s, 1, X + kc(s) * 8192); }
                for (int s = 0; s < 4; s++) ld(s, 1, WE + (size_t)(kt * 8 + 4 * hf + s) * 8192);
                const uint16_t* WCb = WC + (size_t)(kt * 16 + 8 * hf) * 8192;
                mbar_wait(SDONE + 8 * 3, 0); ld(11, 1, WCb + 4 * 8192);
                for (int s = 0; s < 4; s++) ld(4 + s, 1, WCb + s * 8192);
                for (int s = 5; s < 8; s++) ld(s - 5, 2, WCb + s * 8192);
                const uint16_t* Hb = g_H + (size_t)(tt * 16 + 8 * hf) * 8192;
                const unsigned* fl = g_HFLAG + (LAYER * 16 + tt) * 16 + 8 * hf;
                for (int s = 0; s < 8; s++) {
                    const int hs = s == 0 ? 3 : (s == 1 ? 12 : (s < 5 ? 6 + s : s - 1));
                    if (s >= 1 && s <= 4) mbar_wait(SDONE + 8 * (3 + s), 0);
                    unsigned v; int n = 0;
                    do {
                        asm volatile("ld.acquire.gpu.global.u32 %0, [%1];" : "=r"(v) : "l"(fl + s) : "memory");
                        if (++n > (1 << 22)) __trap();
                    } while (v != epoch);
                    fence_async_all();
                    ld(hs, s == 1 ? 1 : 2, Hb + s * 8192);
                }
            }
        } else if (aw <= 2) {
            const int sw = aw - 1, kr = lane & 7;
            float a[16];
#pragma unroll
            for (int i = 0; i < 16; i++) a[i] = 0.f;
#pragma unroll 1
            for (int s = 0; s < 8; s++) {
                const int slot = s < 5 ? 8 + s : 3 + s;
                mbar_wait(FULL + 8 * slot, s < 5 ? 0 : 1);
                const bool dcchunk = ((4 * (1 - hf) + s) & 7) == 0;
#pragma unroll
                for (int k8 = 0; k8 < 8; k8++) {
#pragma unroll
                    for (int i = 0; i < 2; i++) {
                        const int n8 = sw * 8 + (lane >> 3) + 4 * i;
                        uint4 v = *reinterpret_cast<const uint4*>(sm + slot * 16384 + (k8 * 16 + n8) * 128 + kr * 16);
                        if (k8 == 0 && dcchunk && kr == 1) v = make_uint4(0, 0, 0, 0);
                        float f;
                        f = bf_lo(v.x); a[8 * i + 0] = fmaf(f, f, a[8 * i + 0]); f = bf_hi(v.x); a[8 * i + 1] = fmaf(f, f, a[8 * i + 1]);
                        f = bf_lo(v.y); a[8 * i + 2] = fmaf(f, f, a[8 * i + 2]); f = bf_hi(v.y); a[8 * i + 3] = fmaf(f, f, a[8 * i + 3]);
                        f = bf_lo(v.z); a[8 * i + 4] = fmaf(f, f, a[8 * i + 4]); f = bf_hi(v.z); a[8 * i + 5] = fmaf(f, f, a[8 * i + 5]);
                        f = bf_lo(v.w); a[8 * i + 6] = fmaf(f, f, a[8 * i + 6]); f = bf_hi(v.w); a[8 * i + 7] = fmaf(f, f, a[8 * i + 7]);
                    }
                }
                __syncwarp();
                if (lane == 0) mbar_arrive(SDONE + 8 * s);
            }
#pragma unroll
            for (int i = 0; i < 16; i++) {
                a[i] += __shfl_xor_sync(0xffffffffu, a[i], 1);
                a[i] += __shfl_xor_sync(0xffffffffu, a[i], 2);
                a[i] += __shfl_xor_sync(0xffffffffu, a[i], 4);
            }
            if (kr == 0) {
#pragma unroll
                for (int i = 0; i < 2; i++) {
                    const int n8 = sw * 8 + (lane >> 3) + 4 * i;
#pragma unroll
                    for (int e = 0; e < 8; e++) s_rs[n8 * 8 + e] = rsqrtf(a[8 * i + e] * (1.f / 512.f) + 1e-5f);
                }
            }
            __syncwarp();
            if (lane == 0) mbar_arrive(RSBAR);
        }
    } else {
        asm volatile("setmaxnreg.inc.sync.aligned.u32 216;");
        const int w = tid >> 7, ww = (tid >> 5) & 3, lane = tid & 31, g = lane >> 2, q = lane & 3;
        const bool elect = (tid & 127) == 0;
        const int ch = pt * 64 + w * 32 + ww * 8 + g;
        float2 lam, coef;
        {
            float lr = __bfloat162float(Lre[ch]), li = __bfloat162float(Lim[ch]);
            float dt = __bfloat162float(__float2bfloat16_rn(expf(__bfloat162float(logdt[ch]))));
            float er = expf(dt * lr), sn, cs;
            sincosf(dt * li, &sn, &cs);
            lam = make_float2(er * cs, er * sn);
            float inv = 1.f / (lr * lr + li * li), nr = lam.x - 1.f, ni = lam.y;
            coef = make_float2((nr * lr + ni * li) * inv, (ni * lr - nr * li) * inv);
        }
        float acc[64], acc2[64];
#pragma unroll
        for (int i = 0; i < 64; i++) { acc[i] = 0.f; acc2[i] = 0.f; }
#pragma unroll 1
        for (int s = 0; s < 8; s++) {
            const int xs = s < 5 ? 8 + s : 3 + s;
            mbar_wait(FULL + 8 * s, 0);
            mbar_wait(FULL + 8 * xs, s < 5 ? 0 : 1);
            wg_fence();
#pragma unroll
            for (int kk = 0; kk < 4; kk++)
                mma128_ss<1>(acc, mkdesc(sb + s * 16384 + w * 1024 + kk * 4096, 2048, 128), mkdesc(sb + xs * 16384 + kk * 4096, 2048, 128), 1);
            wg_commit();
            if (s > 0) {
                wg_wait<1>();
                if (elect) { mbar_arrive(EMPTY + 8 * (s - 1)); if (s - 1 < 4) mbar_arrive(EMPTY + 8 * (8 + s - 1)); }
            }
        }
#pragma unroll 1
        for (int s = 0; s < 4; s++) {
            const int xs = s == 0 ? 12 : 7 + s;
            mbar_wait(FULL + 8 * s, 1);
            wg_fence();
#pragma unroll
            for (int kk = 0; kk < 4; kk++)
                mma128_ss<1>(acc2, mkdesc(sb + s * 16384 + w * 1024 + kk * 4096, 2048, 128), mkdesc(sb + xs * 16384 + kk * 4096, 2048, 128), 1);
        }
        wg_commit();
        wg_wait<1>();
        reg_fence(acc);
        if (elect) mbar_arrive(EMPTY + 8 * 7);
        mbar_wait(RSBAR, 0);
#pragma unroll
        for (int j = 0; j < 16; j++) {
            float2 r = *reinterpret_cast<const float2*>(s_rs + 8 * j + 2 * q);
            float vr = acc[4 * j], vi = acc[4 * j + 2];
            acc[4 * j] = (coef.x * vr - coef.y * vi) * r.x; acc[4 * j + 2] = (coef.x * vi + coef.y * vr) * r.x;
            vr = acc[4 * j + 1]; vi = acc[4 * j + 3];
            acc[4 * j + 1] = (coef.x * vr - coef.y * vi) * r.y; acc[4 * j + 3] = (coef.x * vi + coef.y * vr) * r.y;
        }
        float2 E = make_float2(0.f, 0.f);
#pragma unroll
        for (int j = 0; j < 16; j++) {
            E = cfma(lam, E, make_float2(acc[4 * j], acc[4 * j + 2]));
            E = cfma(lam, E, make_float2(acc[4 * j + 1], acc[4 * j + 3]));
        }
        float2 l32 = lam;
#pragma unroll
        for (int i = 0; i < 5; i++) l32 = cmul(l32, l32);
        const float2 l64 = cmul(l32, l32), l128 = cmul(l64, l64);
        float2 I = E;
        {
            float2 t = make_float2(__shfl_up_sync(0xffffffffu, I.x, 1, 4), __shfl_up_sync(0xffffffffu, I.y, 1, 4));
            if (q >= 1) I = cfma(l32, t, I);
            t = make_float2(__shfl_up_sync(0xffffffffu, I.x, 2, 4), __shfl_up_sync(0xffffffffu, I.y, 2, 4));
            if (q >= 2) I = cfma(l64, t, I);
        }
        uint4* agg = g_AGG + (LAYER * 16) * 512 + ch;
        if (q == 3 && tt < 15) {
            asm volatile("st.relaxed.gpu.global.v4.u32 [%0], {%1,%2,%3,%4};" ::"l"(agg + tt * 512), "r"(__float_as_uint(I.x)), "r"(epoch), "r"(__float_as_uint(I.y)), "r"(epoch) : "memory");
        }
        float2 cq = make_float2(__shfl_up_sync(0xffffffffu, I.x, 1, 4), __shfl_up_sync(0xffffffffu, I.y, 1, 4));
        if (q == 0) cq = make_float2(0.f, 0.f);
        float2 part = make_float2(0.f, 0.f);
        {
            const float2 l256 = cmul(l128, l128), l512 = cmul(l256, l256);
            uint4 a[4];
            int n = 0;
            bool ok;
            do {
                ok = true;
#pragma unroll
                for (int i = 0; i < 4; i++) {
                    int tp = tt - 1 - q - 4 * i;
                    if (tp >= 0) {
                        asm volatile("ld.relaxed.gpu.global.v4.u32 {%0,%1,%2,%3}, [%4];" : "=r"(a[i].x), "=r"(a[i].y), "=r"(a[i].z), "=r"(a[i].w) : "l"(agg + tp * 512) : "memory");
                        ok = ok && a[i].y == epoch && a[i].w == epoch;
                    } else a[i] = make_uint4(0, 0, 0, 0);
                }
                if (++n > (1 << 22)) __trap();
            } while (!ok);
#pragma unroll
            for (int i = 3; i >= 0; i--) part = cfma(l512, part, make_float2(__uint_as_float(a[i].x), __uint_as_float(a[i].z)));
            float2 pw = q == 0 ? make_float2(1.f, 0.f) : (q == 1 ? l128 : (q == 2 ? l256 : cmul(l256, l128)));
            part = cmul(pw, part);
            part.x += __shfl_xor_sync(0xffffffffu, part.x, 1); part.y += __shfl_xor_sync(0xffffffffu, part.y, 1);
            part.x += __shfl_xor_sync(0xffffffffu, part.x, 2); part.y += __shfl_xor_sync(0xffffffffu, part.y, 2);
        }
        {
            float2 pw = q == 0 ? make_float2(1.f, 0.f) : (q == 1 ? l32 : (q == 2 ? l64 : cmul(l64, l32)));
            float2 h = cfma(pw, part, cq);
            uint32_t* hp = reinterpret_cast<uint32_t*>(g_H + (size_t)(tt * 16 + 2 * pt + w) * 8192) + (2 * ww) * 512 + g * 4 + q;
#pragma unroll
            for (int j = 0; j < 16; j++) {
                float2 h0 = cfma(lam, h, make_float2(acc[4 * j], acc[4 * j + 2]));
                h = cfma(lam, h0, make_float2(acc[4 * j + 1], acc[4 * j + 3]));
                hp[j * 32] = pack_bf16(h0.x, h.x);
                hp[512 + j * 32] = pack_bf16(h0.y, h.y);
            }
        }
        fence_async_all();
        bar_sync(2 + w, 128);
        if (elect) {
            __threadfence();
            asm volatile("st.release.gpu.global.u32 [%0], %1;" ::"l"(g_HFLAG + (LAYER * 16 + tt) * 16 + 2 * pt + w), "r"(epoch) : "memory");
        }
        wg_wait<0>();
        reg_fence(acc2);
        if (elect) {
            mbar_arrive(EMPTY + 0); mbar_arrive(EMPTY + 8); mbar_arrive(EMPTY + 16); mbar_arrive(EMPTY + 24);
            mbar_arrive(EMPTY + 8 * 12); mbar_arrive(EMPTY + 8 * 8); mbar_arrive(EMPTY + 8 * 9); mbar_arrive(EMPTY + 8 * 10);
        }
        const int m0 = kt * 128 + w * 64 + ww * 16 + g;
        float D0 = 0.f, D1 = 0.f;
        if (LAYER == 1) { D0 = __bfloat162float(Dsk[m0]); D1 = __bfloat162float(Dsk[m0 + 8]); }
#pragma unroll
        for (int j = 0; j < 16; j++) {
            float2 r = *reinterpret_cast<const float2*>(s_rs + 8 * j + 2 * q);
            if (LAYER == 0) {
                acc2[4 * j] *= r.x; acc2[4 * j + 1] *= r.y; acc2[4 * j + 2] *= r.x; acc2[4 * j + 3] *= r.y;
            } else {
                acc2[4 * j] *= fmaf(r.x, D0, 1.f); acc2[4 * j + 1] *= fmaf(r.y, D0, 1.f);
                acc2[4 * j + 2] *= fmaf(r.x, D1, 1.f); acc2[4 * j + 3] *= fmaf(r.y, D1, 1.f);
            }
        }
#pragma unroll 1
        for (int s = 0; s < 8; s++) {
            const int as = s < 4 ? 4 + s : (s == 4 ? 11 : s - 5);
            const int hs = s == 0 ? 3 : (s == 1 ? 12 : (s < 5 ? 6 + s : s - 1));
            mbar_wait(FULL + 8 * as, s < 5 ? 1 : 0);
            mbar_wait(FULL + 8 * hs, s == 1 ? 1 : 0);
            wg_fence();
#pragma unroll
            for (int kk = 0; kk < 4; kk++)
                mma128_ss<1>(acc2, mkdesc(sb + as * 16384 + w * 1024 + kk * 4096, 2048, 128), mkdesc(sb + hs * 16384 + kk * 4096, 2048, 128), 1);
            wg_commit();
            if (s > 0 && s <= 3) {
                wg_wait<1>();
                if (elect) mbar_arrive(EMPTY + 8 * (4 + s - 1));
            }
        }
        wg_wait<0>();
        reg_fence(acc2);
        uint32_t peer_rdy, peer_dat, peer_buf;
        asm("mapa.shared::cluster.u32 %0, %1, %2;" : "=r"(peer_rdy) : "r"(PRDY), "r"(1 - hf));
        asm("mapa.shared::cluster.u32 %0, %1, %2;" : "=r"(peer_dat) : "r"(PDAT), "r"(1 - hf));
        asm("mapa.shared::cluster.u32 %0, %1, %2;" : "=r"(peer_buf) : "r"(sb), "r"(1 - hf));
        mbar_arrive_remote(peer_rdy);
        mbar_wait_cluster(PRDY, 0);
#pragma unroll
        for (int i = 0; i < 8; i++) {
            float a0 = hf ? acc2[4 * i] : acc2[32 + 4 * i], a1 = hf ? acc2[4 * i + 1] : acc2[32 + 4 * i + 1];
            float a2 = hf ? acc2[4 * i + 2] : acc2[32 + 4 * i + 2], a3 = hf ? acc2[4 * i + 3] : acc2[32 + 4 * i + 3];
            asm volatile("st.shared::cluster.v4.f32 [%0], {%1,%2,%3,%4};" ::"r"(peer_buf + (i * 256 + tid) * 16), "f"(a0), "f"(a1), "f"(a2), "f"(a3) : "memory");
        }
        mbar_arrive_remote(peer_dat);
        mbar_wait_cluster(PDAT, 0);
        float v[32];
#pragma unroll
        for (int i = 0; i < 8; i++) {
            float4 o = *reinterpret_cast<const float4*>(sm + (i * 256 + tid) * 16);
            v[2 * i] = o.x + (hf ? acc2[32 + 4 * i] : acc2[4 * i]);
            v[2 * i + 1] = o.y + (hf ? acc2[32 + 4 * i + 1] : acc2[4 * i + 1]);
            v[16 + 2 * i] = o.z + (hf ? acc2[32 + 4 * i + 2] : acc2[4 * i + 2]);
            v[16 + 2 * i + 1] = o.w + (hf ? acc2[32 + 4 * i + 3] : acc2[4 * i + 3]);
        }
        if (LAYER == 0) {
            finalize_freq<true>(v, kt, tt, hf, sred, tid);
        } else {
            const int t0 = tt * 128 + q * 32 + hf * 16;
#pragma unroll
            for (int i = 0; i < 16; i++) {
                float mr = g_XF[2048 + t0 + i] * 0.044194173824159220275f * s_rs[8 * (8 * hf + (i >> 1)) + 2 * q + (i & 1)];
                out[(size_t)(t0 + i) * 512 + m0] = v[i] - mr * D0;
                out[(size_t)(t0 + i) * 512 + m0 + 8] = v[16 + i] - mr * D1;
            }
        }
    }
}

extern "C" void kernel_launch(void* const* d_in, const int* in_sizes, int n_in, void* d_out, int out_size) {
    (void)in_sizes; (void)n_in; (void)out_size;
    static bool init = false;
    if (!init) {
        cudaFuncSetAttribute(kw_kernel, cudaFuncAttributeMaxDynamicSharedMemorySize, KW_SMEM);
        cudaFuncSetAttribute(k0_kernel, cudaFuncAttributeMaxDynamicSharedMemorySize, K0_SMEM);
        cudaFuncSetAttribute(kc_kernel, cudaFuncAttributeMaxDynamicSharedMemorySize, KC_SMEM);
        cudaFuncSetAttribute(ks_kernel<0>, cudaFuncAttributeMaxDynamicSharedMemorySize, KS_SMEM);
        cudaFuncSetAttribute(ks_kernel<1>, cudaFuncAttributeMaxDynamicSharedMemorySize, KS_SMEM);
        init = true;
    }
    const uint16_t* x = (const uint16_t*)d_in[0];
    const uint16_t* wr = (const uint16_t*)d_in[1];
    const uint16_t* wi = (const uint16_t*)d_in[2];
    const __nv_bfloat16* Lre = (const __nv_bfloat16*)d_in[4];
    const __nv_bfloat16* Lim = (const __nv_bfloat16*)d_in[5];
    const uint16_t* Bre = (const uint16_t*)d_in[6];
    const uint16_t* Bim = (const uint16_t*)d_in[7];
    const uint16_t* Cre = (const uint16_t*)d_in[8];
    const uint16_t* Cim = (const uint16_t*)d_in[9];
    const __nv_bfloat16* logdt = (const __nv_bfloat16*)d_in[10];
    const __nv_bfloat16* Dsk = (const __nv_bfloat16*)d_in[11];
    float* out = (float*)d_out;
    kw_kernel<<<96, 256, KW_SMEM>>>(Bre, Bim, Cre, Cim, (const uint16_t*)Dsk);
    k0_kernel<<<128, 256, K0_SMEM>>>(x, wr, wi);
    kc_kernel<<<128, 256, KC_SMEM>>>();
    ks_kernel<0><<<128, 384, KS_SMEM>>>(Lre, Lim, logdt, Dsk, out);
    kc_kernel<<<128, 256, KC_SMEM>>>();
    ks_kernel<1><<<128, 384, KS_SMEM>>>(Lre, Lim, logdt, Dsk, out);
}
```

```cpp
#include <cuda_runtime.h>
#include <cuda.h>
#include <cuda_bf16.h>
#include <stdint.h>

namespace tb {
constexpr double PI = 3.14159265358979323846264338327950288;
constexpr double ccos_small(double x) { double x2 = x * x, term = 1.0, s = 1.0; for (int i = 1; i < 14; i++) { term *= -x2 / ((2 * i - 1) * (2 * i)); s += term; } return s; }
constexpr double csin_small(double x) { double x2 = x * x, term = x, s = x; for (int i = 1; i < 14; i++) { term *= -x2 / ((2 * i) * (2 * i + 1)); s += term; } return s; }
constexpr double cos2pi(int i, int N) {
    i %= N; if (i < 0) i += N;
    if (i > N / 2) i = N - i;
    bool neg = false; if (i > N / 4) { i = N / 2 - i; neg = true; }
    double r = (i <= N / 8) ? ccos_small(2 * PI * i / N) : csin_small(2 * PI * (N / 4 - i) / N);
    return neg ? -r : r;
}
constexpr double sin2pi(int i, int N) { return cos2pi(i - N / 4, N); }
constexpr uint16_t to_bf16(double v) {
    if (v == 0.0) return 0;
    uint16_t sign = v < 0 ? 0x8000 : 0; if (v < 0) v = -v;
    int e = 0; while (v >= 2.0) { v *= 0.5; e++; } while (v < 1.0) { v *= 2.0; e--; }
    double m = (v - 1.0) * 128.0; int mi = (int)m; double fr = m - mi;
    if (fr > 0.5 || (fr == 0.5 && (mi & 1))) mi++;
    if (mi == 128) { mi = 0; e++; }
    return sign | (uint16_t)((e + 127) << 7) | (uint16_t)mi;
}
struct Cos512 { uint16_t v[512]; constexpr Cos512() : v() { for (int i = 0; i < 512; i++) v[i] = to_bf16(cos2pi(i, 512) / 16.0); } };
template <bool TRANS> struct QTab {
    uint16_t v[512 * 512];
    constexpr QTab() : v() {
        Cos512 c; uint16_t dc = to_bf16(0.044194173824159220275), ndc = dc | 0x8000;
        for (int k = 0; k < 512; k++) {
            int s = k >> 1; int off = (k & 1) ? 128 : 0;
            for (int d = 0; d < 512; d++) {
                uint16_t val = (k == 0) ? ((d & 1) ? ndc : dc) : (k == 1) ? dc : c.v[(s * d + off) & 511];
                int r = TRANS ? d : k, kk = TRANS ? k : d;
                v[((((r >> 7) * 8 + (kk >> 6)) * 8 + ((kk & 63) >> 3)) * 16 + ((r & 127) >> 3)) * 64 + (r & 7) * 8 + (kk & 7)] = val;
            }
        }
    }
};
struct FTab {
    uint16_t v[4096 + 8192];
    constexpr FTab() : v() {
        for (int m = 0; m < 64; m++) for (int kk = 0; kk < 64; kk++) {
            int f1 = (m >> 4) * 8 + (m & 7), c = (m >> 3) & 1;
            int t1 = (kk >> 4) * 8 + (kk & 7), cp = (kk >> 3) & 1;
            double co = cos2pi(t1 * f1, 32), si = sin2pi(t1 * f1, 32);
            double val = (c == 0) ? (cp == 0 ? co : si) : (cp == 0 ? -si : co);
            v[((kk >> 3) * 8 + (m >> 3)) * 64 + (m & 7) * 8 + (kk & 7)] = to_bf16(val);
        }
        for (int kk = 0; kk < 64; kk++) for (int n = 0; n < 128; n++) {
            int jj = n >> 3, q = (n >> 1) & 3, c = n & 1;
            int f2 = 8 * (jj >> 1) + 2 * q + (jj & 1);
            double val = c == 0 ? cos2pi(kk * f2, 64) : -sin2pi(kk * f2, 64);
            v[4096 + ((kk >> 3) * 16 + (n >> 3)) * 64 + (n & 7) * 8 + (kk & 7)] = to_bf16(val);
        }
    }
};
}

__device__ __align__(1024) constexpr tb::QTab<false> g_T1 = tb::QTab<false>();
__device__ __align__(1024) constexpr tb::QTab<true> g_T2 = tb::QTab<true>();
__device__ __align__(1024) constexpr tb::FTab g_T3 = tb::FTab();

__device__ __align__(1024) uint16_t g_XT[512 * 2048];
__device__ __align__(1024) uint16_t g_XB[16 * 8 * 8192];
__device__ __align__(1024) uint16_t g_H[16 * 16 * 8192];
__device__ __align__(1024) uint16_t g_WB[8 * 8 * 8192];
__device__ __align__(1024) uint16_t g_WC1[4 * 16 * 8192];
__device__ __align__(1024) uint16_t g_WC2[4 * 16 * 8192];
__device__ __align__(1024) uint16_t g_WE1[4 * 8 * 8192];
__device__ __align__(1024) uint32_t g_WF[256 * 2048];
__device__ __align__(16) float g_SSQ[2 * 2048];
__device__ __align__(16) uint4 g_PST[2 * 16 * 8 * 64];
__device__ __align__(16) uint4 g_AGG[2 * 16 * 512];
__device__ unsigned g_HFLAG[2 * 16 * 16];
__device__ unsigned g_epoch;
__device__ __align__(16) uint2 g_DH[1024];
__device__ unsigned g_GB[16 * 32];
#define TS(kid, i)
#define TSG(kid, i)

__device__ __forceinline__ uint32_t smem_u32(const void* p) { return (uint32_t)__cvta_generic_to_shared(p); }
__device__ __forceinline__ uint64_t mkdesc(uint32_t addr, uint32_t lbo, uint32_t sbo) {
    return (uint64_t)((addr & 0x3FFFF) >> 4) | ((uint64_t)(lbo >> 4) << 16) | ((uint64_t)(sbo >> 4) << 32);
}
__device__ __forceinline__ void mbar_init(uint32_t a, int c) { asm volatile("mbarrier.init.shared::cta.b64 [%0], %1;" ::"r"(a), "r"(c)); }
__device__ __forceinline__ void mbar_expect(uint32_t a, int bytes) { asm volatile("mbarrier.arrive.expect_tx.shared::cta.b64 _, [%0], %1;" ::"r"(a), "r"(bytes) : "memory"); }
__device__ __forceinline__ void mbar_arrive(uint32_t a) { asm volatile("mbarrier.arrive.shared::cta.b64 _, [%0];" ::"r"(a) : "memory"); }
__device__ __forceinline__ void mbar_arrive_remote(uint32_t ra) { asm volatile("mbarrier.arrive.relaxed.cluster.shared::cluster.b64 _, [%0];" ::"r"(ra) : "memory"); }
__device__ __forceinline__ uint32_t mapa(uint32_t a, uint32_t r) { uint32_t o; asm("mapa.shared::cluster.u32 %0, %1, %2;" : "=r"(o) : "r"(a), "r"(r)); return o; }
__device__ __forceinline__ void bulk_s2g(void* dst, uint32_t src, int bytes) {
    asm volatile("cp.async.bulk.global.shared::cta.bulk_group [%0], [%1], %2;" ::"l"(dst), "r"(src), "r"(bytes) : "memory");
}
__device__ __forceinline__ void bulk_commit() { asm volatile("cp.async.bulk.commit_group;" ::: "memory"); }
__device__ __forceinline__ void bulk_wait_all() { asm volatile("cp.async.bulk.wait_group 0;" ::: "memory"); }
__device__ __forceinline__ void sts128(uint32_t a, float x, float y, float z, float w) { asm volatile("st.shared.v4.f32 [%0], {%1,%2,%3,%4};" ::"r"(a), "f"(x), "f"(y), "f"(z), "f"(w) : "memory"); }
__device__ __forceinline__ float4 lds128(uint32_t a) { float4 v; asm volatile("ld.shared.v4.f32 {%0,%1,%2,%3}, [%4];" : "=f"(v.x), "=f"(v.y), "=f"(v.z), "=f"(v.w) : "r"(a) : "memory"); return v; }
__device__ __forceinline__ void sts32(uint32_t a, uint32_t v) { asm volatile("st.shared.u32 [%0], %1;" ::"r"(a), "r"(v) : "memory"); }
__device__ __forceinline__ bool mbar_try(uint32_t a, int ph) {
    uint32_t ok;
    asm volatile("{\n.reg .pred p;\nmbarrier.try_wait.parity.shared::cta.b64 p, [%1], %2;\nselp.u32 %0, 1, 0, p;\n}" : "=r"(ok) : "r"(a), "r"(ph) : "memory");
    return ok;
}
__device__ __forceinline__ void mbar_wait(uint32_t a, int ph) {
    int n = 0;
    while (!mbar_try(a, ph)) { if (++n > (1 << 22)) break; }
}
__device__ __forceinline__ void bulk_g2s(uint32_t dst, const void* src, int bytes, uint32_t bar) {
    asm volatile("cp.async.bulk.shared::cluster.global.mbarrier::complete_tx::bytes [%0], [%1], %2, [%3];" ::"r"(dst), "l"(src), "r"(bytes), "r"(bar) : "memory");
}
__device__ __forceinline__ uint64_t mkdesc_sw(uint32_t addr) {
    return (uint64_t)((addr & 0x3FFFF) >> 4) | ((uint64_t)1 << 16) | ((uint64_t)64 << 32) | ((uint64_t)1 << 62);
}
__device__ __forceinline__ void tma2d(uint32_t dst, const CUtensorMap* m, int c0, int c1, uint32_t bar) {
    asm volatile("cp.async.bulk.tensor.2d.shared::cluster.global.mbarrier::complete_tx::bytes [%0], [%1, {%2, %3}], [%4];"
                 ::"r"(dst), "l"(m), "r"(c0), "r"(c1), "r"(bar) : "memory");
}
__device__ __forceinline__ void tma4d(uint32_t dst, const CUtensorMap* m, int c0, int c1, int c2, int c3, uint32_t bar) {
    asm volatile("cp.async.bulk.tensor.4d.shared::cluster.global.mbarrier::complete_tx::bytes [%0], [%1, {%2, %3, %4, %5}], [%6];"
                 ::"r"(dst), "l"(m), "r"(c0), "r"(c1), "r"(c2), "r"(c3), "r"(bar) : "memory");
}
__device__ __forceinline__ void tma_st3(const CUtensorMap* m, uint32_t src, int c0, int c1, int c2) {
    asm volatile("cp.async.bulk.tensor.3d.global.shared::cta.bulk_group [%0, {%2, %3, %4}], [%1];" ::"l"(m), "r"(src), "r"(c0), "r"(c1), "r"(c2) : "memory");
}
__device__ __forceinline__ void tma_st5(const CUtensorMap* m, uint32_t src, int c0, int c1, int c2, int c3, int c4) {
    asm volatile("cp.async.bulk.tensor.5d.global.shared::cta.bulk_group [%0, {%2, %3, %4, %5, %6}], [%1];" ::"l"(m), "r"(src), "r"(c0), "r"(c1), "r"(c2), "r"(c3), "r"(c4) : "memory");
}
__device__ __forceinline__ void fence_async_smem() { asm volatile("fence.proxy.async.shared::cta;" ::: "memory"); }
__device__ __forceinline__ void fence_async_all() { asm volatile("fence.proxy.async;" ::: "memory"); }
__device__ __forceinline__ void bar_sync(int id, int n) { asm volatile("bar.sync %0, %1;" ::"r"(id), "r"(n) : "memory"); }
__device__ __forceinline__ void wg_fence() { asm volatile("wgmma.fence.sync.aligned;" ::: "memory"); }
__device__ __forceinline__ void wg_commit() { asm volatile("wgmma.commit_group.sync.aligned;" ::: "memory"); }
template <int N> __device__ __forceinline__ void wg_wait() { asm volatile("wgmma.wait_group.sync.aligned %0;" ::"n"(N) : "memory"); }
template <int N> __device__ __forceinline__ void reg_fence(float (&d)[N]) {
#pragma unroll
    for (int i = 0; i < N; i++) asm volatile("" : "+f"(d[i])::"memory");
}
__device__ __forceinline__ uint32_t pack_bf16(float lo, float hi) {
    uint32_t r; asm("cvt.rn.bf16x2.f32 %0, %1, %2;" : "=r"(r) : "f"(hi), "f"(lo)); return r;
}
__device__ __forceinline__ float bf_lo(uint32_t u) { return __uint_as_float(u << 16); }
__device__ __forceinline__ float bf_hi(uint32_t u) { return __uint_as_float(u & 0xffff0000u); }

#define ACC8(d, o) "+f"(d[o + 0]), "+f"(d[o + 1]), "+f"(d[o + 2]), "+f"(d[o + 3]), "+f"(d[o + 4]), "+f"(d[o + 5]), "+f"(d[o + 6]), "+f"(d[o + 7])
#define ACC32(d) ACC8(d, 0), ACC8(d, 8), ACC8(d, 16), ACC8(d, 24)
#define ACC64(d) ACC32(d), ACC8(d, 32), ACC8(d, 40), ACC8(d, 48), ACC8(d, 56)
#define R32 "{%0,%1,%2,%3,%4,%5,%6,%7,%8,%9,%10,%11,%12,%13,%14,%15,%16,%17,%18,%19,%20,%21,%22,%23,%24,%25,%26,%27,%28,%29,%30,%31}"
#define R64 "{%0,%1,%2,%3,%4,%5,%6,%7,%8,%9,%10,%11,%12,%13,%14,%15,%16,%17,%18,%19,%20,%21,%22,%23,%24,%25,%26,%27,%28,%29,%30,%31,%32,%33,%34,%35,%36,%37,%38,%39,%40,%41,%42,%43,%44,%45,%46,%47,%48,%49,%50,%51,%52,%53,%54,%55,%56,%57,%58,%59,%60,%61,%62,%63}"

#define OUT8(d, o) "=f"(d[o + 0]), "=f"(d[o + 1]), "=f"(d[o + 2]), "=f"(d[o + 3]), "=f"(d[o + 4]), "=f"(d[o + 5]), "=f"(d[o + 6]), "=f"(d[o + 7])
#define OUT32(d) OUT8(d, 0), OUT8(d, 8), OUT8(d, 16), OUT8(d, 24)
#define OUT64(d) OUT32(d), OUT8(d, 32), OUT8(d, 40), OUT8(d, 48), OUT8(d, 56)
template <int TB> __device__ __forceinline__ void mma128_ss0(float (&d)[64], uint64_t da, uint64_t db) {
    asm volatile("{\n.reg .pred p;\nsetp.ne.b32 p, 0, 0;\n"
                 "wgmma.mma_async.sync.aligned.m64n128k16.f32.bf16.bf16 " R64 ", %64, %65, p, 1, 1, 0, %66;\n}\n"
                 : OUT64(d) : "l"(da), "l"(db), "n"(TB));
}
template <int TB> __device__ __forceinline__ void mma64_ss0(float (&d)[32], uint64_t da, uint64_t db) {
    asm volatile("{\n.reg .pred p;\nsetp.ne.b32 p, 0, 0;\n"
                 "wgmma.mma_async.sync.aligned.m64n64k16.f32.bf16.bf16 " R32 ", %32, %33, p, 1, 1, 0, %34;\n}\n"
                 : OUT32(d) : "l"(da), "l"(db), "n"(TB));
}
__device__ __forceinline__ void mma128_rs0(float (&d)[64], uint32_t a0, uint32_t a1, uint32_t a2, uint32_t a3, uint64_t db) {
    asm volatile("{\n.reg .pred p;\nsetp.ne.b32 p, 0, 0;\n"
                 "wgmma.mma_async.sync.aligned.m64n128k16.f32.bf16.bf16 " R64 ", {%64,%65,%66,%67}, %68, p, 1, 1, 0;\n}\n"
                 : OUT64(d) : "r"(a0), "r"(a1), "r"(a2), "r"(a3), "l"(db));
}
template <int TB> __device__ __forceinline__ void mma128_ss(float (&d)[64], uint64_t da, uint64_t db, int acc) {
    asm volatile("{\n.reg .pred p;\nsetp.ne.b32 p, %66, 0;\n"
                 "wgmma.mma_async.sync.aligned.m64n128k16.f32.bf16.bf16 " R64 ", %64, %65, p, 1, 1, 0, %67;\n}\n"
                 : ACC64(d) : "l"(da), "l"(db), "r"(acc), "n"(TB));
}
template <int TB> __device__ __forceinline__ void mma64_ss(float (&d)[32], uint64_t da, uint64_t db, int acc) {
    asm volatile("{\n.reg .pred p;\nsetp.ne.b32 p, %34, 0;\n"
                 "wgmma.mma_async.sync.aligned.m64n64k16.f32.bf16.bf16 " R32 ", %32, %33, p, 1, 1, 0, %35;\n}\n"
                 : ACC32(d) : "l"(da), "l"(db), "r"(acc), "n"(TB));
}
__device__ __forceinline__ void mma128_rs(float (&d)[64], uint32_t a0, uint32_t a1, uint32_t a2, uint32_t a3, uint64_t db, int acc) {
    asm volatile("{\n.reg .pred p;\nsetp.ne.b32 p, %69, 0;\n"
                 "wgmma.mma_async.sync.aligned.m64n128k16.f32.bf16.bf16 " R64 ", {%64,%65,%66,%67}, %68, p, 1, 1, 0;\n}\n"
                 : ACC64(d) : "r"(a0), "r"(a1), "r"(a2), "r"(a3), "l"(db), "r"(acc));
}

constexpr int SL = 16384;
constexpr int MISC = 13 * SL + 64;
constexpr int OFF_BAR = MISC, OFF_RS = MISC + 1024, OFF_RED = MISC + 1536;
constexpr int OFF_MEAN = OFF_RED + 4608, OFF_BIGRS = OFF_MEAN + 512, OFF_XBST = 11 * SL;
constexpr int OFF_WRXD = OFF_BIGRS + 8192;
constexpr int MK_SMEM = OFF_WRXD + 4096;
enum { B_T1 = 0, B_WRAW = 4, B_WDONE, B_OPB, B_OPC, B_OPD, B_PRDY0, B_PDAT0, B_PRDYW = B_PDAT0 + 2, B_PDATW, B_PDATB, B_BDEAD = B_PDATB + 2, B_BOUT, B_AUXD, B_DONE,
       B_XFF = B_DONE + 4, B_T3F = B_XFF + 2, B_WFF = B_T3F + 2, B_KS = B_WFF + 2 };
enum { K_FULL = 0, K_EMPTY = 13, K_SDONE = 26, K_RSBAR, K_PRDY, K_XDONE, K_HS0, K_HS1, K_PUB, K_PDAT, K_N = K_PDAT + 2 };
constexpr int NBAR = B_KS + 2 * K_N;

__device__ __forceinline__ float2 cmul(float2 a, float2 b) { return make_float2(a.x * b.x - a.y * b.y, a.x * b.y + a.y * b.x); }
__device__ __forceinline__ float2 cfma(float2 a, float2 b, float2 c) { return make_float2(fmaf(a.x, b.x, fmaf(-a.y, b.y, c.x)), fmaf(a.x, b.y, fmaf(a.y, b.x, c.y))); }
__device__ __forceinline__ void gb_arrive(int i) {
    __threadfence();
    fence_async_all();
    asm volatile("red.relaxed.gpu.global.add.u32 [%0], 1;" ::"l"(g_GB + i * 32) : "memory");
}
__device__ __forceinline__ void gb_wait(int i, unsigned target, bool live = true) {
    unsigned v; int n = live ? 0 : (1 << 22);
    do {
        asm volatile("ld.acquire.gpu.global.u32 %0, [%1];" : "=r"(v) : "l"(g_GB + i * 32) : "memory");
        if (++n > (1 << 22)) break;
    } while ((int)(v - target) < 0);
}

struct Maps { CUtensorMap x, bre, bim, cre, cim, xb, wf; };
struct Params {
    const uint16_t *x, *wr, *wi, *Bre, *Bim, *Cre, *Cim, *Dsk16;
    const __nv_bfloat16 *Lre, *Lim, *logdt, *Dsk;
    float* out;
};

__device__ __forceinline__ void sts128u(uint32_t a, uint32_t x, uint32_t y, uint32_t z, uint32_t w) { asm volatile("st.shared.v4.u32 [%0], {%1,%2,%3,%4};" ::"r"(a), "r"(x), "r"(y), "r"(z), "r"(w) : "memory"); }
__device__ __forceinline__ uint4 lds128u(uint32_t a) { uint4 v; asm volatile("ld.shared.v4.u32 {%0,%1,%2,%3}, [%4];" : "=r"(v.x), "=r"(v.y), "=r"(v.z), "=r"(v.w) : "r"(a) : "memory"); return v; }
__device__ __forceinline__ void st_async4(uint32_t ra, uint32_t x, uint32_t y, uint32_t z, uint32_t w, uint32_t rbar) {
    asm volatile("st.async.weak.shared::cluster.mbarrier::complete_tx::bytes.v4.u32 [%0], {%1,%2,%3,%4}, [%5];" ::"r"(ra), "r"(x), "r"(y), "r"(z), "r"(w), "r"(rbar) : "memory");
}
__device__ __forceinline__ void exchange(float (&acc)[64], float (&v)[32], int hf, int tid, uint32_t rcv, uint32_t prdy, uint32_t pdat, bool f32, bool go = true) {
    const int t = tid & 127;
    const uint32_t pr = mapa(rcv, 1 - hf) + t * 16, pd = mapa(pdat, 1 - hf);
    if (go) mbar_wait(prdy, 0);
    if (f32) {
#pragma unroll
        for (int i = 0; i < 8; i++)
            st_async4(pr + i * 2048, __float_as_uint(hf ? acc[8 * i] : acc[8 * i + 2]), __float_as_uint(hf ? acc[8 * i + 1] : acc[8 * i + 3]),
                      __float_as_uint(hf ? acc[8 * i + 4] : acc[8 * i + 6]), __float_as_uint(hf ? acc[8 * i + 5] : acc[8 * i + 7]), pd);
    } else {
#pragma unroll
        for (int i = 0; i < 4; i++) {
            uint32_t o[4];
#pragma unroll
            for (int e = 0; e < 4; e++) o[e] = pack_bf16(hf ? acc[16 * i + 4 * e] : acc[16 * i + 4 * e + 2], hf ? acc[16 * i + 4 * e + 1] : acc[16 * i + 4 * e + 3]);
            if (go) st_async4(pr + i * 2048, o[0], o[1], o[2], o[3], pd);
        }
    }
#pragma unroll
    for (int j = 0; j < 16; j++) { v[2 * j] = hf ? acc[4 * j + 2] : acc[4 * j]; v[2 * j + 1] = hf ? acc[4 * j + 3] : acc[4 * j + 1]; }
    if (go) mbar_wait(pdat, 0);
    if (f32) {
#pragma unroll
        for (int i = 0; i < 8; i++) {
            float4 o = lds128(rcv + (i * 128 + t) * 16);
            v[4 * i] += o.x; v[4 * i + 1] += o.y; v[4 * i + 2] += o.z; v[4 * i + 3] += o.w;
        }
    } else {
#pragma unroll
        for (int i = 0; i < 4; i++) {
            uint4 o = lds128u(rcv + (i * 128 + t) * 16);
            v[8 * i] += bf_lo(o.x); v[8 * i + 1] += bf_hi(o.x); v[8 * i + 2] += bf_lo(o.y); v[8 * i + 3] += bf_hi(o.y);
            v[8 * i + 4] += bf_lo(o.z); v[8 * i + 5] += bf_hi(o.z); v[8 * i + 6] += bf_lo(o.w); v[8 * i + 7] += bf_hi(o.w);
        }
    }
}

__device__ __forceinline__ void finalize_freq(float (&v)[32], int kt, int tt, int hf, uint32_t xt  , float* sred  , int tid, float* ssq, int gb, uint32_t done, bool live) {
    const int w = tid >> 7, ww = (tid >> 5) & 3, lane = tid & 31, g = lane >> 2, q = lane & 3;
    const int k = kt * 128 + w * 64 + ww * 16 + g + 8 * hf;
    const int sw = (q >> 1) | ((g & 1) << 1);
    const uint32_t row = xt + w * 8192 + (ww * 8 + g) * 256 + q * 64;
#pragma unroll
    for (int i = 0; i < 4; i++) {
        uint32_t o[4];
#pragma unroll
        for (int e = 0; e < 4; e++) {
            o[e] = pack_bf16(v[8 * i + 2 * e], v[8 * i + 2 * e + 1]);
            v[8 * i + 2 * e] = bf_lo(o[e]); v[8 * i + 2 * e + 1] = bf_hi(o[e]);
        }
        sts128u(row + ((i ^ sw) << 4), o[0], o[1], o[2], o[3]);
    }
    fence_async_smem();
    const float m0 = (k == 1) ? 0.f : 1.f;
#pragma unroll
    for (int i = 0; i < 32; i++) v[i] = m0 * v[i] * v[i];
#pragma unroll
    for (int i = 0; i < 16; i++) {
        bool up = lane & 16;
        float send = up ? v[i] : v[i + 16], keep = up ? v[i + 16] : v[i];
        v[i] = keep + __shfl_xor_sync(0xffffffffu, send, 16);
    }
#pragma unroll
    for (int i = 0; i < 8; i++) {
        bool up = lane & 8;
        float send = up ? v[i] : v[i + 8], keep = up ? v[i + 8] : v[i];
        v[i] = keep + __shfl_xor_sync(0xffffffffu, send, 8);
    }
#pragma unroll
    for (int i = 0; i < 4; i++) {
        bool up = lane & 4;
        float send = up ? v[i] : v[i + 4], keep = up ? v[i + 4] : v[i];
        v[i] = keep + __shfl_xor_sync(0xffffffffu, send, 4);
    }
    const int to = ((lane >> 4) & 1) * 16 + ((lane >> 3) & 1) * 8 + ((lane >> 2) & 1) * 4;
    *reinterpret_cast<float4*>(sred + (tid >> 5) * 128 + q * 32 + to) = make_float4(v[0], v[1], v[2], v[3]);
    bar_sync(1, 256);
    if (tid < 128) {
        if (tid == 0 && live) { bulk_s2g(g_XT + (size_t)((tt * 4 + kt) * 2 + hf) * 8192, xt, 16384); bulk_commit(); }
        float a = 0.f;
#pragma unroll
        for (int i = 0; i < 8; i++) a += sred[i * 128 + tid];
        const int t = tt * 128 + tid;
        sred[1024 + ((tid & 64) | ((((t >> 3) ^ (t >> 6)) & 7) << 3) | (t & 7))] = a;
        fence_async_smem();
        bar_sync(5, 128);
        if (tid == 0) {
            if (live) asm volatile("cp.reduce.async.bulk.global.shared::cta.bulk_group.add.f32 [%0], [%1], 512;" ::"l"(ssq + tt * 128), "r"(smem_u32(sred + 1024)) : "memory");
            bulk_commit();
            bulk_wait_all();
            if (live) asm volatile("red.release.gpu.global.add.u32 [%0], 1;" ::"l"(g_GB + gb * 32) : "memory");
            mbar_arrive(done);
        }
        __syncwarp();
    }
}

__device__ __forceinline__ void p0_compute(const Params& P, const Maps& M, unsigned char* sm, uint32_t sb, int tid, int b, unsigned target, bool live) {
    const int tt = b >> 3, kt = (b >> 1) & 3, hf = b & 1;
    const uint32_t BAR = sb + OFF_BAR;
    float* sred = reinterpret_cast<float*>(sm + OFF_RED);
    const int w = tid >> 7;
    if (tid == 0 && live) {
#pragma unroll 1
        for (int i = 1; i < 4; i++) {
            mbar_expect(BAR + 8 * (B_T1 + i), 32768);
            tma4d(sb + (8 + i) * SL, &M.x, hf * 256 + i * 64, 0, 4 * tt, 0, BAR + 8 * (B_T1 + i));
            bulk_g2s(sb + i * SL, g_T1.v + (kt * 8 + 4 * hf + i) * 8192, 16384, BAR + 8 * (B_T1 + i));
        }
    }
    __syncwarp();
    float acc[64];
#pragma unroll
    for (int dc = 0; dc < 4; dc++) {
        if (live) mbar_wait(BAR + 8 * (B_T1 + dc), 0);
        if (tid == 0 && dc == 0) TS(0, 1);
        wg_fence();
#pragma unroll
        for (int kk = 0; kk < 4; kk++) {
            const uint64_t da = mkdesc(sb + dc * SL + w * 1024 + kk * 4096, 2048, 128), db = mkdesc_sw(sb + (8 + dc) * SL + kk * 32);
            if (dc == 0 && kk == 0) mma128_ss0<0>(acc, da, db); else mma128_ss<0>(acc, da, db, 1);
        }
        wg_commit();
        if (dc == 1) {
            wg_wait<1>();
            asm volatile("barrier.cluster.wait.aligned;" ::: "memory");
            if ((tid & 127) == 0 && live) mbar_arrive_remote(mapa(BAR + 8 * B_PRDY0, 1 - hf));
        }
    }
    wg_wait<0>();
    reg_fence(acc);
    if (tid == 0) TS(0, 2);
    float v[32];
    exchange(acc, v, hf, tid, sb + 8 * SL + w * 8192, BAR + 8 * B_PRDY0, BAR + 8 * (B_PDAT0 + w), false, live);
    if (tid == 0) TS(0, 3);
    bar_sync(1, 256);
    finalize_freq(v, kt, tt, hf, sb + 9 * SL, sred, tid, g_SSQ, 0, BAR + 8 * B_DONE, live);
    if (tid == 0) TS(0, 4);
    {
        if (live) mbar_wait(BAR + 8 * B_WRAW, 0);
        const uint16_t* swr = reinterpret_cast<const uint16_t*>(sm + 12 * SL);
        const uint16_t* swi = swr + 4112;
#pragma unroll
        for (int i = 0; i < 4; i++) {
            const int u = i * 256 + tid, qt = u & 3, slot = u >> 2, col = slot == 0 ? 256 : slot;
            uint32_t o[4];
#pragma unroll
            for (int e = 0; e < 4; e++) o[e] = (uint32_t)swr[(4 * qt + e) * 257 + col] | ((uint32_t)swi[(4 * qt + e) * 257 + col] << 16);
            sts128u(sb + 11 * SL + u * 16, o[0], o[1], o[2], o[3]);
        }
        fence_async_smem();
        bar_sync(1, 256);
        if (tid == 36 && live) {
            const int f2 = b >> 1;
            tma_st3(&M.wf, sb + 11 * SL, 0, (2 * (f2 >> 3) + (f2 & 1)) * 8 + ((f2 >> 1) & 3) * 2 + (b & 1), 0);
            bulk_commit();
        }
        __syncwarp();
    }
    {
        const int ww = (tid >> 5) & 3, lane = tid & 31, g = lane >> 2, q = lane & 3, t = tid & 127;
        asm volatile("" : "+r"(sb));
        float a[32];
        if (live) mbar_wait(BAR + 8 * B_OPB, 0);
        wg_fence();
#pragma unroll
        for (int dc = 0; dc < 4; dc++)
#pragma unroll
            for (int kk = 0; kk < 4; kk++) {
                const uint64_t da = mkdesc_sw(sb + 4 * SL + dc * 8192 + kk * 32), db = mkdesc(sb + dc * SL + w * 1024 + kk * 4096, 2048, 128);
                if (dc == 0 && kk == 0) mma64_ss0<0>(a, da, db); else mma64_ss<0>(a, da, db, 1);
            }
        wg_commit();
        if (tid == 36 && live) { bulk_wait_all(); asm volatile("red.release.gpu.global.add.u32 [%0], 1;" ::"l"(g_GB + 6 * 32) : "memory"); TS(0, 7); }
        __syncwarp();
        wg_wait<0>();
        reg_fence(a);
        if (t == 0) mbar_arrive(BAR + 8 * B_BDEAD);
        const uint32_t prx = mapa(sb + 10 * SL + w * 8192, 1 - hf) + t * 16, pd = mapa(BAR + 8 * (B_PDATB + w), 1 - hf);
#pragma unroll
        for (int i = 0; i < 4; i++)
            if (live) st_async4(prx + i * 2048, __float_as_uint(hf ? a[8 * i] : a[8 * i + 2]), __float_as_uint(hf ? a[8 * i + 1] : a[8 * i + 3]),
                      __float_as_uint(hf ? a[8 * i + 4] : a[8 * i + 6]), __float_as_uint(hf ? a[8 * i + 5] : a[8 * i + 7]), pd);
        if (live) mbar_wait(BAR + 8 * (B_PDATB + w), 0);
        const uint32_t so = sb + 8 * SL + w * 4096 + (ww & 1) * 256 + (ww >> 1) * 128 + g * 16 + q * 4;
#pragma unroll
        for (int i = 0; i < 4; i++) {
            float4 o = lds128(sb + 10 * SL + w * 8192 + t * 16 + i * 2048);
            float v0 = o.x + (hf ? a[8 * i + 2] : a[8 * i]), v1 = o.y + (hf ? a[8 * i + 3] : a[8 * i + 1]);
            float v2 = o.z + (hf ? a[8 * i + 6] : a[8 * i + 4]), v3 = o.w + (hf ? a[8 * i + 7] : a[8 * i + 5]);
            if (i == 0 && kt == 0 && w == 0 && q == 0) v1 = 0.f;
            sts32(so + (2 * i) * 512, pack_bf16(v0, v1)); sts32(so + (2 * i + 1) * 512, pack_bf16(v2, v3));
        }
        fence_async_smem();
        bar_sync(2 + w, 128);
        if (lane < 4 && live) {
            const int pc = ww * 4 + lane, k8 = pc >> 1, pr = pc & 1;
            bulk_s2g(g_WB + (size_t)((tt >> 1) * 8 + 2 * kt + w) * 8192 + k8 * 1024 + ((tt & 1) * 8 + pr * 4 + hf * 2) * 64, sb + 8 * SL + w * 4096 + pc * 256, 256);
            bulk_commit();
        }
        __syncwarp();
        if (tid == 0) TS(0, 9);
    }
}

__device__ __forceinline__ void l2_prefetch(const void* p, int bytes) {
    asm volatile("cp.async.bulk.prefetch.L2.global [%0], %1;" ::"l"(p), "r"(bytes) : "memory");
}
__device__ __forceinline__ void p0_aux(const Params& P, const Maps& M, unsigned char* sm, uint32_t sb, int at, int b, unsigned target, bool live) {
    const int tt = b >> 3, kt = (b >> 1) & 3, hf = b & 1;
    const uint32_t BAR = sb + OFF_BAR;
    const int ww = at >> 5, lane = at & 31, g = lane >> 2, q = lane & 3;
    if (!live) {
    } else if (at == 0) {
        bulk_g2s(sb + 12 * SL, P.wr + (size_t)b * 4112, 8224, BAR + 8 * B_WRAW);
        bulk_g2s(sb + 12 * SL + 8224, P.wi + (size_t)b * 4112, 8224, BAR + 8 * B_WRAW);
    } else if (at == 32) {
        if (live) mbar_wait(BAR + 8 * (B_T1 + 1), 0);
        for (int i = 0; i < 4; i++) tma2d(sb + 6 * SL + i * 8192, (tt & 1) ? &M.cim : &M.cre, (tt >> 1) * 64, hf * 256 + i * 64, BAR + 8 * B_OPC);
    } else if (at == 96) {
        if (live) mbar_wait(BAR + 8 * (B_T1 + 2), 0);
        for (int i = 0; i < 4; i++) {
            tma2d(sb + 4 * SL + i * 8192, &M.bre, hf * 256 + i * 64, tt * 32, BAR + 8 * B_OPB);
            tma2d(sb + 4 * SL + i * 8192 + 4096, &M.bim, hf * 256 + i * 64, tt * 32, BAR + 8 * B_OPB);
        }
    } else if (at == 64) {
        l2_prefetch(g_T2.v + (size_t)b * 2048, 4096);
        if (b < 6) l2_prefetch(g_T3.v + b * 2048, 4096);
    }
    __syncwarp();
    if (at == 0) TS(7, 1);
    {
        float* sd = reinterpret_cast<float*>(sm + OFF_WRXD);
        const uint2 dd = *reinterpret_cast<const uint2*>(P.Dsk16 + 4 * at);
        const float dv[4] = {bf_lo(dd.x), bf_hi(dd.x), bf_lo(dd.y), bf_hi(dd.y)};
#pragma unroll 1
        for (int i = 0; i < 4; i++) {
            float c = 0.f, sn = 0.f;
#pragma unroll
            for (int e = 0; e < 4; e++) {
                int idx = ((4 * b + i) * (4 * at + e)) & 511;
                if (idx >= 256) idx -= 512;
                float s0, c0;
                __sincosf((float)idx * (6.283185307179586f / 512.f), &s0, &c0);
                c = fmaf(dv[e], c0, c); sn = fmaf(dv[e], s0, sn);
            }
#pragma unroll
            for (int o = 16; o > 0; o >>= 1) { c += __shfl_xor_sync(0xffffffffu, c, o); sn += __shfl_xor_sync(0xffffffffu, sn, o); }
            if (lane == 0) { sd[ww * 8 + i] = c; sd[ww * 8 + 4 + i] = sn; }
        }
        bar_sync(4, 128);
        if (at < 8 && live) {
            const float a = (sd[at] + sd[8 + at]) + (sd[16 + at] + sd[24 + at]);
            asm volatile("st.relaxed.gpu.global.v2.u32 [%0], {%1,%2};" ::"l"(g_DH + (at >> 2) * 512 + 4 * b + (at & 3)), "r"(__float_as_uint(a)), "r"(target) : "memory");
        }
    }
    if (at == 0) TS(7, 2);
#define PKH(A, j) pack_bf16(hf ? A[4 * (j)] : A[4 * (j) + 2], hf ? A[4 * (j) + 1] : A[4 * (j) + 3])
#define PKO(A, j) pack_bf16(hf ? A[4 * (j) + 2] : A[4 * (j)], hf ? A[4 * (j) + 3] : A[4 * (j) + 1])
    uint32_t ownC[16];
    if (live) mbar_wait(BAR + 8 * (B_T1 + 3), 0); if (live) mbar_wait(BAR + 8 * (B_T1 + 2), 0); if (live) mbar_wait(BAR + 8 * (B_T1 + 1), 0); if (live) mbar_wait(BAR + 8 * B_T1, 0);
    if (live) mbar_wait(BAR + 8 * B_OPC, 0);
    const uint32_t pdw = mapa(BAR + 8 * B_PDATW, 1 - hf);
    const uint32_t prx = mapa(sb + 6 * SL, 1 - hf) + at * 16;
    {
        float a0[32], a1[32];
        wg_fence();
#pragma unroll
        for (int dc = 0; dc < 4; dc++)
#pragma unroll
            for (int kk = 0; kk < 4; kk++) {
                const uint64_t db = mkdesc_sw(sb + 6 * SL + dc * 8192 + kk * 2048);
                const uint64_t d0 = mkdesc(sb + dc * SL + kk * 4096, 2048, 128), d1 = mkdesc(sb + dc * SL + 1024 + kk * 4096, 2048, 128);
                if (dc == 0 && kk == 0) { mma64_ss0<1>(a0, d0, db); mma64_ss0<1>(a1, d1, db); } else { mma64_ss<1>(a0, d0, db, 1); mma64_ss<1>(a1, d1, db, 1); }
            }
        wg_commit();
        bar_sync(4, 128);
        {
            uint4 r[4]; int n = live ? 0 : (1 << 22); bool ok;
            do {
                ok = true;
#pragma unroll
                for (int i = 0; i < 4; i++) {
                    asm volatile("ld.relaxed.gpu.global.v4.u32 {%0,%1,%2,%3}, [%4];" : "=r"(r[i].x), "=r"(r[i].y), "=r"(r[i].z), "=r"(r[i].w) : "l"(g_DH + (i * 128 + at) * 2) : "memory");
                    ok = ok && r[i].y == target && r[i].w == target;
                }
                if (++n > (1 << 22)) break;
            } while (!ok);
#pragma unroll
            for (int i = 0; i < 4; i++) *reinterpret_cast<uint2*>(sm + OFF_WRXD + (i * 128 + at) * 8) = make_uint2(r[i].x, r[i].z);
        }
        __syncwarp();
        asm volatile("barrier.cluster.wait.aligned;" ::: "memory");
        wg_wait<0>();
        reg_fence(a0); reg_fence(a1);
        if (at == 0) TS(7, 3);
        uint32_t snd[16];
#pragma unroll
        for (int j = 0; j < 8; j++) { ownC[j] = PKO(a0, j); ownC[8 + j] = PKO(a1, j); snd[j] = PKH(a0, j); snd[8 + j] = PKH(a1, j); }
        bar_sync(4, 128);
        if (at == 0 && live) mbar_arrive_remote(mapa(BAR + 8 * B_PRDYW, 1 - hf));
        if (live) mbar_wait(BAR + 8 * B_PRDYW, 0);
#pragma unroll
        for (int i = 0; i < 4; i++) if (live) st_async4(prx + i * 2048, snd[4 * i], snd[4 * i + 1], snd[4 * i + 2], snd[4 * i + 3], pdw);
        if (at == 0) TS(7, 4);
    }
    if (at == 96 && live) {
        mbar_wait(BAR + 8 * B_BDEAD, 0);
        gb_wait(4, target);
        const uint32_t FULL = BAR + 8 * B_KS;
        const int pt = b & 7;
        for (int s = 0; s < 6; s++) {
            const int kcs = s < 4 ? 4 * (1 - hf) + ((s + kt) & 3) : 4 * hf + (s - 4);
            mbar_expect(FULL + 8 * s, 16384);
            bulk_g2s(sb + s * SL, g_WB + (size_t)(pt * 8 + kcs) * 8192, 16384, FULL + 8 * s);
        }
    }
    __syncwarp();
    {
        const float* Ct = reinterpret_cast<const float*>(sm + OFF_WRXD);
        const float* St = Ct + 512;
        const int ktd = b >> 5, jc = (b >> 2) & 7, j8b = (b & 3) * 2;
#pragma unroll
        for (int i = 0; i < 2; i++) {
            const int u = i * 128 + at;
            const int k = ktd * 128 + (u & 127), j0 = jc * 64 + (j8b + i) * 8;
            const int fk = k == 0 ? 256 : (k >> 1); const bool sk = (k > 1) && (k & 1);
            const float ak = k < 2 ? 0.044194173824159220275f : 0.0625f;
            float val[8];
#pragma unroll
            for (int e = 0; e < 8; e++) {
                const int j = j0 + e;
                const int fj = j == 0 ? 256 : (j >> 1); const bool sj = (j > 1) && (j & 1);
                const float aj = j < 2 ? 0.044194173824159220275f : 0.0625f;
                const int dm = (fk - fj) & 511, dp = (fk + fj) & 511;
                float r;
                if (sk == sj) r = sk ? (Ct[dm] - Ct[dp]) : (Ct[dm] + Ct[dp]);
                else r = sk ? -(St[dp] + St[dm]) : -(St[dp] - St[dm]);
                val[e] = j == 1 ? 0.f : 0.5f * ak * aj * r;
            }
            sts128u(sb + 7 * SL + u * 16, pack_bf16(val[0], val[1]), pack_bf16(val[2], val[3]), pack_bf16(val[4], val[5]), pack_bf16(val[6], val[7]));
        }
        fence_async_smem();
        bar_sync(4, 128);
        if (at == 32 && live) { bulk_s2g(g_WE1 + (size_t)b * 2048, sb + 7 * SL, 4096); bulk_commit(); }
        __syncwarp();
        if (at == 0) TS(7, 5);
    }
    if (at == 0) TS(0, 10);
    if (live) mbar_wait(BAR + 8 * B_PDATW, 0);
    if (at == 0) TS(0, 11);
    {
        const uint32_t rcv = sb + 6 * SL + at * 16;
#pragma unroll
        for (int mh = 0; mh < 2; mh++) {
            uint32_t* oC = reinterpret_cast<uint32_t*>(g_WC1) + (size_t)(kt * 16 + (tt & ~1)) * 4096 + (tt & 1) * 512 + (8 * mh + 2 * ww + hf) * 32 + g * 4 + q;
#pragma unroll
            for (int i = 0; i < 2; i++) {
                uint4 o = lds128u(rcv + (2 * mh + i) * 2048);
                const uint32_t r[4] = {o.x, o.y, o.z, o.w};
#pragma unroll
                for (int e = 0; e < 4; e++) {
                    const int j = 4 * i + e;
                    const float sc = (tt & 1) ? -2.f : 2.f;
                    if (live) oC[(j >> 2) * 4096 + (j & 3) * 1024] = pack_bf16(sc * (bf_lo(r[e]) + bf_lo(ownC[8 * mh + j])), sc * (bf_hi(r[e]) + bf_hi(ownC[8 * mh + j])));
                }
            }
        }
    }
    bar_sync(4, 128);
    if (at == 32 && live) { bulk_wait_all(); gb_arrive(7); mbar_arrive(BAR + 8 * B_AUXD); TS(0, 5); }
    if (ww > 0) {
        if (b < 32 && ww > 1 && live) g_SSQ[2048 + b * 64 + at - 64] = 0.f;
#pragma unroll 3
        for (int i = at - 32; i < 512; i += 96) {
            const int u = b * 512 + i;
            int mr = u & 7, m8 = (u >> 3) & 15, p8 = (u >> 7) & 7, pc = (u >> 10) & 15, dt = u >> 14;
            int d = dt * 128 + m8 * 8 + mr, c = p8 & 1, ch8 = pc * 4 + (p8 >> 1);
            uint4 v = *reinterpret_cast<const uint4*>((c ? P.Cim : P.Cre) + d * 512 + ch8 * 8);
            __nv_bfloat162 s = __float2bfloat162_rn(c ? -2.f : 2.f);
            __nv_bfloat162* p = reinterpret_cast<__nv_bfloat162*>(&v);
#pragma unroll
            for (int k = 0; k < 4; k++) p[k] = __hmul2(p[k], s);
            if (live) reinterpret_cast<uint4*>(g_WC2)[u] = v;
        }
        bar_sync(6, 96);
        if (at == 96 && live) gb_arrive(5);
        __syncwarp();
    }
}

__device__ __forceinline__ void kc_compute(const Maps& M, unsigned char* sm, uint32_t sb, int tid, int b, int which, unsigned target, bool live) {
    asm volatile("" : "+r"(sb), "+r"(tid), "+r"(b));
    const int kid = 1 + 3 * which; (void)kid;
    const uint32_t BAR = sb + OFF_BAR;
    const int w = tid >> 7, ww = (tid >> 5) & 3, lane = tid & 31, g = lane >> 2, q = lane & 3;
    const uint32_t sT = sb + 8 * SL, sX = sb + 9 * SL + 8192, sR = sb + OFF_BIGRS, sD = sb + 12 * SL + w * 8192;
    const int slot = 2 * b + w;
    const int t1 = ww * 8 + g;
    if (tid == 0) {
        TS(kid, 0); TSG(kid, 30);
    }
    float twc[16], tws[16];
#pragma unroll
    for (int i = 0; i < 16; i++) {
        int t2 = 8 * (i >> 1) + 2 * q + (i & 1);
        int idx = t1 * t2;
        if (idx >= 1024) idx -= 2048;
        float a = (float)idx * (-6.283185307179586f / 2048.f);
        __sincosf(a, &tws[i], &twc[i]);
    }
    if (which == 0 && lane < 4) { bulk_wait_all(); __threadfence(); mbar_arrive(BAR + 8 * B_BOUT); }
    __syncwarp();
    if (tid == 0) gb_wait(2 * which, target, live);
    if (tid == 32) {
        if (which == 0) { mbar_wait(BAR + 8 * B_BOUT, 0); if (live) asm volatile("red.release.gpu.global.add.u32 [%0], 1;" ::"l"(g_GB + 4 * 32) : "memory"); }
        mbar_expect(BAR + 8 * (B_T3F + which), 24576);
        bulk_g2s(sT, g_T3.v, 24576, BAR + 8 * (B_T3F + which));
        if (which == 1) {
            mbar_expect(BAR + 8 * (B_WFF + which), 16384);
            bulk_g2s(sb + OFF_XBST, g_WF + (size_t)b * 4096, 16384, BAR + 8 * (B_WFF + which));
        }
    }
    bar_sync(1, 256);
    if (tid == 0) TS(kid, 5);
    if (lane < 2) {
        const int ttl = (tid >> 5) * 2 + lane, k0 = 4 * b;
        bulk_g2s(sX + ttl * 1056, g_XT + (size_t)(((ttl * 4 + (k0 >> 7)) * 2 + ((k0 >> 3) & 1)) * 2 + ((k0 >> 6) & 1)) * 4096 + (((k0 >> 4) & 3) * 8 + (k0 & 7)) * 128,
                 1024, BAR + 8 * (B_XFF + which));
    }
    if (tid == 66) { bulk_g2s(sR, g_SSQ + which * 2048, 8192, BAR + 8 * (B_XFF + which)); }
    if (tid == 98 && which == 0) {
        gb_wait(6, target, live);
        mbar_expect(BAR + 8 * B_WFF, 16384);
        bulk_g2s(sb + OFF_XBST, g_WF + (size_t)b * 4096, 16384, BAR + 8 * B_WFF);
    }
    __syncwarp();
    if (tid == 0) TS(kid, 6);
    mbar_wait(BAR + 8 * (B_XFF + which), 0);
    if (tid == 0) TS(kid, 1);
    float2 xr[8], xi[8];
    const uint32_t xrow = sX + (t1 >> 1) * 1056 + w * 512 + q * 4;
    const float zi = slot == 0 ? 0.f : 1.f;
#pragma unroll
    for (int j = 0; j < 8; j++) {
        const int qp = 2 * (t1 & 1) + (j >> 2), i = j & 3;
        uint32_t ur, ui; float2 r;
        asm volatile("ld.shared.u32 %0, [%1];" : "=r"(ur) : "r"(xrow + (4 * qp + (i ^ (qp >> 1))) * 16));
        asm volatile("ld.shared.u32 %0, [%1];" : "=r"(ui) : "r"(xrow + 256 + (4 * qp + (i ^ ((qp >> 1) | 2))) * 16));
        asm volatile("ld.shared.v2.f32 {%0,%1}, [%2];" : "=f"(r.x), "=f"(r.y) : "r"(sR + (t1 * 64 + 8 * (j ^ g) + 2 * q) * 4));
        r.x = rsqrtf(r.x * (1.f / 512.f) + 1e-5f); r.y = rsqrtf(r.y * (1.f / 512.f) + 1e-5f);
        xr[j] = make_float2(bf_lo(ur), bf_hi(ur)); xi[j] = make_float2(bf_lo(ui), bf_hi(ui));
        sts32(sD + ((2 * ww) * 8 + j) * 128 + g * 16 + q * 4, pack_bf16(xr[j].x * r.x, xr[j].y * r.y));
        sts32(sD + ((2 * ww + 1) * 8 + j) * 128 + g * 16 + q * 4, pack_bf16(xi[j].x * r.x * zi, xi[j].y * r.y * zi));
    }
    fence_async_smem();
    bar_sync(2 + w, 128);
    mbar_wait(BAR + 8 * (B_T3F + which), 0);
    if (tid == 0) TS(kid, 2);
    uint32_t af[16], wf[16];
    {
        float d1[32];
        wg_fence();
#pragma unroll
        for (int kk = 0; kk < 4; kk++) {
            if (kk == 0) mma64_ss0<1>(d1, mkdesc(sT, 1024, 128), mkdesc(sD, 1024, 128));
            else mma64_ss<1>(d1, mkdesc(sT + kk * 2048, 1024, 128), mkdesc(sD + kk * 2048, 1024, 128), 1);
        }
        wg_commit();
        mbar_wait(BAR + 8 * (B_WFF + which), 0);
#pragma unroll
        for (int i = 0; i < 16; i++) asm volatile("ld.shared.u32 %0, [%1];" : "=r"(wf[i]) : "r"(sb + OFF_XBST + (w * 2048 + i * 128 + q * 32 + t1) * 4));
        wg_wait<0>();
        reg_fence(d1);
#pragma unroll
        for (int j = 0; j < 8; j++) {
            float r0 = d1[4 * j], r1 = d1[4 * j + 1], i0 = d1[4 * j + 2], i1 = d1[4 * j + 3];
            float c0 = twc[2 * j], s0 = tws[2 * j], c1 = twc[2 * j + 1], s1 = tws[2 * j + 1];
            af[2 * j] = pack_bf16(r0 * c0 - i0 * s0, r1 * c1 - i1 * s1);
            af[2 * j + 1] = pack_bf16(r0 * s0 + i0 * c0, r1 * s1 + i1 * c1);
        }
    }
    float acc[64];
    wg_fence();
#pragma unroll
    for (int kb = 0; kb < 4; kb++) {
        if (kb == 0) mma128_rs0(acc, af[0], af[1], af[2], af[3], mkdesc(sT + 8192, 2048, 128));
        else mma128_rs(acc, af[4 * kb], af[4 * kb + 1], af[4 * kb + 2], af[4 * kb + 3], mkdesc(sT + 8192 + kb * 4096, 2048, 128), 1);
    }
    wg_commit();
    wg_wait<0>();
    reg_fence(acc);
    {
        float yr[16], yi[16];
#pragma unroll
        for (int jj = 0; jj < 16; jj++) {
            float r = acc[4 * jj] - acc[4 * jj + 3], i = acc[4 * jj + 1] + acc[4 * jj + 2];
            float a = bf_lo(wf[jj]) * (1.f / 2048.f), c = bf_hi(wf[jj]) * (1.f / 2048.f);
            yr[jj] = r * a - i * c; yi[jj] = r * c + i * a;
        }
#pragma unroll
        for (int kb = 0; kb < 4; kb++) {
            af[4 * kb] = pack_bf16(yr[4 * kb], yr[4 * kb + 1]);
            af[4 * kb + 1] = pack_bf16(yi[4 * kb], yi[4 * kb + 1]);
            af[4 * kb + 2] = pack_bf16(yr[4 * kb + 2], yr[4 * kb + 3]);
            af[4 * kb + 3] = pack_bf16(yi[4 * kb + 2], yi[4 * kb + 3]);
        }
    }
    wg_fence();
#pragma unroll
    for (int kb = 0; kb < 4; kb++) {
        if (kb == 0) mma128_rs0(acc, af[0], af[1], af[2], af[3], mkdesc(sT + 8192, 2048, 128));
        else mma128_rs(acc, af[4 * kb], af[4 * kb + 1], af[4 * kb + 2], af[4 * kb + 3], mkdesc(sT + 8192 + kb * 4096, 2048, 128), 1);
    }
    wg_commit();
    bar_sync(2 + w, 128);
    wg_wait<0>();
    reg_fence(acc);
#pragma unroll
    for (int j = 0; j < 8; j++) {
        float r0 = acc[8 * j] + acc[8 * j + 3], i0 = acc[8 * j + 2] - acc[8 * j + 1];
        float r1 = acc[8 * j + 4] + acc[8 * j + 7], i1 = acc[8 * j + 6] - acc[8 * j + 5];
        float c0 = twc[2 * j], s0 = tws[2 * j], c1 = twc[2 * j + 1], s1 = tws[2 * j + 1];
        sts32(sD + ((2 * ww) * 8 + j) * 128 + g * 16 + q * 4, pack_bf16(r0 * c0 + i0 * s0, r1 * c1 + i1 * s1));
        sts32(sD + ((2 * ww + 1) * 8 + j) * 128 + g * 16 + q * 4, pack_bf16(r0 * s0 - i0 * c0, r1 * s1 - i1 * c1));
    }
    fence_async_smem();
    bar_sync(2 + w, 128);
    {
        float d4[32];
        wg_fence();
#pragma unroll
        for (int kk = 0; kk < 4; kk++) {
            if (kk == 0) mma64_ss0<1>(d4, mkdesc(sT, 1024, 128), mkdesc(sD, 1024, 128));
            else mma64_ss<1>(d4, mkdesc(sT + kk * 2048, 1024, 128), mkdesc(sD + kk * 2048, 1024, 128), 1);
        }
        wg_commit();
        wg_wait<0>();
        reg_fence(d4);
        if (tid == 0) TS(kid, 3);
#pragma unroll
        for (int j = 0; j < 8; j++) {
            xr[j].x += d4[4 * j]; xr[j].y += d4[4 * j + 1];
            xi[j].x -= zi * d4[4 * j + 2]; xi[j].y -= zi * d4[4 * j + 3];
        }
    }
    bar_sync(1, 256);
    if (tid == 0) TS(kid, 7);
    {
        const int tt = 4 * ww + (g >> 1);
        const uint32_t stg = sb + OFF_XBST + tt * 1024;
#pragma unroll
        for (int c = 0; c < 2; c++) {
#pragma unroll
            for (int j = 0; j < 4; j++) {
                const uint32_t p0 = c ? pack_bf16(xi[j].x, xi[j].y) : pack_bf16(xr[j].x, xr[j].y);
                const uint32_t p1 = c ? pack_bf16(xi[j + 4].x, xi[j + 4].y) : pack_bf16(xr[j + 4].x, xr[j + 4].y);
                asm volatile("st.shared.v2.u32 [%0], {%1,%2};" ::"r"(stg + (4 * j + q) * 64 + (2 * w + c) * 16 + (g & 1) * 8), "r"(p0), "r"(p1) : "memory");
            }
        }
    }
    fence_async_smem();
    bar_sync(1, 256);
    if (tid == 0) {
        TS(kid, 8);
        if (live) tma_st5(&M.xb, sb + OFF_XBST, 0, 0, 0, b & 1, b >> 1);
        bulk_commit();
        TS(kid, 9);
        bulk_wait_all();
        TS(kid, 10);
        if (live) asm volatile("red.release.gpu.global.add.u32 [%0], 1;" ::"l"(g_GB + (1 + 2 * which) * 32) : "memory");
        mbar_arrive(BAR + 8 * (B_DONE + 1 + 2 * which)); TS(kid, 4); TSG(kid, 31);
    }
}

__device__ __forceinline__ void ks_compute(const Params& P, const Maps& M, unsigned char* sm, uint32_t sb, int tid, int b, int LAYER, unsigned epoch, float2 lam, float2 coef, bool live) {
    asm volatile("" : "+r"(sb), "+r"(tid), "+r"(b));
    const int kid = 2 + LAYER; (void)kid;
    const int tt = b >> 3, pt = b & 7, kt = pt >> 1, hf = pt & 1;
    const uint32_t KB = sb + OFF_BAR + 8 * (B_KS + LAYER * K_N);
    const uint32_t FULL = KB + 8 * K_FULL, EMPTY = KB + 8 * K_EMPTY, RSBAR = KB + 8 * K_RSBAR, PRDY = KB + 8 * K_PRDY, PDAT = KB + 8 * K_PDAT,
                   XDONE = KB + 8 * K_XDONE, HS0 = KB + 8 * K_HS0;
    float* s_rs = reinterpret_cast<float*>(sm + OFF_RS);
    float* sred = reinterpret_cast<float*>(sm + OFF_RED);
    const int w = tid >> 7, ww = (tid >> 5) & 3, lane = tid & 31, g = lane >> 2, q = lane & 3;
    const bool elect = (tid & 127) == 0;
    const int ch = pt * 64 + w * 32 + ww * 8 + g;
    if (tid == 0) { TS(kid, 0); TSG(kid, 30); TS(5 + LAYER, 0); TSG(5 + LAYER, 30); TSG(5 + LAYER, 31); }
    const int m0 = kt * 128 + w * 64 + ww * 16 + g;
    float D0 = 0.f, D1 = 0.f;
    if (LAYER == 1) { D0 = __bfloat162float(P.Dsk[m0]); D1 = __bfloat162float(P.Dsk[m0 + 8]); }
    float2 l32 = lam;
#pragma unroll
    for (int i = 0; i < 5; i++) l32 = cmul(l32, l32);
    const float2 l64 = cmul(l32, l32), l128 = cmul(l64, l64);
    float acc[64], acc2[64];
    {
        mbar_wait(FULL, 0);
        mbar_wait(FULL + 8 * 8, 0);
        if (tid == 0) TS(kid, 2);
        wg_fence();
        mma128_ss0<1>(acc, mkdesc(sb + w * 1024, 2048, 128), mkdesc(sb + 8 * SL, 2048, 128));
#pragma unroll
        for (int kk = 1; kk < 4; kk++) mma128_ss<1>(acc, mkdesc(sb + w * 1024 + kk * 4096, 2048, 128), mkdesc(sb + 8 * SL + kk * 4096, 2048, 128), 1);
        wg_commit();
    }
#pragma unroll 1
    for (int s = 1; s < 8; s++) {
        const int xs = s < 5 ? 8 + s : 3 + s;
        mbar_wait(FULL + 8 * s, 0);
        mbar_wait(FULL + 8 * xs, s < 5 ? 0 : 1);
        wg_fence();
#pragma unroll
        for (int kk = 0; kk < 4; kk++)
            mma128_ss<1>(acc, mkdesc(sb + s * SL + w * 1024 + kk * 4096, 2048, 128), mkdesc(sb + xs * SL + kk * 4096, 2048, 128), 1);
        wg_commit();
        wg_wait<1>();
        if (elect) { mbar_arrive(EMPTY + 8 * (s - 1)); if (s - 1 < 4) mbar_arrive(EMPTY + 8 * (8 + s - 1)); }
    }
    wg_wait<0>();
    reg_fence(acc);
    if (elect) mbar_arrive(EMPTY + 8 * 7);
    if (tid == 0) TS(kid, 3);
    mbar_wait(RSBAR, 0);
    if (tid == 0) TS(kid, 4);
#pragma unroll
    for (int j = 0; j < 16; j++) {
        float2 r = *reinterpret_cast<const float2*>(s_rs + 8 * j + 2 * q);
        float vr = acc[4 * j], vi = acc[4 * j + 2];
        acc[4 * j] = (coef.x * vr - coef.y * vi) * r.x; acc[4 * j + 2] = (coef.x * vi + coef.y * vr) * r.x;
        vr = acc[4 * j + 1]; vi = acc[4 * j + 3];
        acc[4 * j + 1] = (coef.x * vr - coef.y * vi) * r.y; acc[4 * j + 3] = (coef.x * vi + coef.y * vr) * r.y;
    }
    float2 E = make_float2(0.f, 0.f);
#pragma unroll
    for (int j = 0; j < 16; j++) {
        E = cfma(lam, E, make_float2(acc[4 * j], acc[4 * j + 2]));
        E = cfma(lam, E, make_float2(acc[4 * j + 1], acc[4 * j + 3]));
    }
    float2 I = E;
    {
        float2 t = make_float2(__shfl_up_sync(0xffffffffu, I.x, 1, 4), __shfl_up_sync(0xffffffffu, I.y, 1, 4));
        if (q >= 1) I = cfma(l32, t, I);
        t = make_float2(__shfl_up_sync(0xffffffffu, I.x, 2, 4), __shfl_up_sync(0xffffffffu, I.y, 2, 4));
        if (q >= 2) I = cfma(l64, t, I);
    }
    uint4* agg = g_AGG + (LAYER * 16) * 512 + ch;
    if (q == 3 && tt < 15 && live) {
        asm volatile("st.relaxed.gpu.global.v4.u32 [%0], {%1,%2,%3,%4};" ::"l"(agg + tt * 512), "r"(__float_as_uint(I.x)), "r"(epoch), "r"(__float_as_uint(I.y)), "r"(epoch) : "memory");
    }
    if (tid == 0) TS(kid, 5);
    {
        mbar_wait(FULL, 1);
        wg_fence();
        mma128_ss0<1>(acc2, mkdesc(sb + w * 1024, 2048, 128), mkdesc(sb + 12 * SL, 2048, 128));
#pragma unroll
        for (int kk = 1; kk < 4; kk++) mma128_ss<1>(acc2, mkdesc(sb + w * 1024 + kk * 4096, 2048, 128), mkdesc(sb + 12 * SL + kk * 4096, 2048, 128), 1);
        wg_commit();
    }
#pragma unroll 1
    for (int s = 1; s < 4; s++) {
        mbar_wait(FULL + 8 * s, 1);
        wg_fence();
#pragma unroll
        for (int kk = 0; kk < 4; kk++)
            mma128_ss<1>(acc2, mkdesc(sb + s * SL + w * 1024 + kk * 4096, 2048, 128), mkdesc(sb + (7 + s) * SL + kk * 4096, 2048, 128), 1);
        wg_commit();
    }
    float2 cq = make_float2(__shfl_up_sync(0xffffffffu, I.x, 1, 4), __shfl_up_sync(0xffffffffu, I.y, 1, 4));
    if (q == 0) cq = make_float2(0.f, 0.f);
    float2 part = make_float2(0.f, 0.f);
    {
        const float2 l256 = cmul(l128, l128), l512 = cmul(l256, l256);
        uint4 a[4];
        int n = live ? 0 : (1 << 22);
        bool ok;
        do {
            ok = true;
#pragma unroll
            for (int i = 0; i < 4; i++) {
                int tp = tt - 1 - q - 4 * i;
                if (tp >= 0) {
                    asm volatile("ld.relaxed.gpu.global.v4.u32 {%0,%1,%2,%3}, [%4];" : "=r"(a[i].x), "=r"(a[i].y), "=r"(a[i].z), "=r"(a[i].w) : "l"(agg + tp * 512) : "memory");
                    ok = ok && a[i].y == epoch && a[i].w == epoch;
                } else a[i] = make_uint4(0, 0, 0, 0);
            }
            if (++n > (1 << 22)) break;
        } while (!ok);
#pragma unroll
        for (int i = 3; i >= 0; i--) part = cfma(l512, part, make_float2(__uint_as_float(a[i].x), __uint_as_float(a[i].z)));
        float2 pw = q == 0 ? make_float2(1.f, 0.f) : (q == 1 ? l128 : (q == 2 ? l256 : cmul(l256, l128)));
        part = cmul(pw, part);
        part.x += __shfl_xor_sync(0xffffffffu, part.x, 1); part.y += __shfl_xor_sync(0xffffffffu, part.y, 1);
        part.x += __shfl_xor_sync(0xffffffffu, part.x, 2); part.y += __shfl_xor_sync(0xffffffffu, part.y, 2);
    }
    if (tid == 0) TS(kid, 6);
    const int stslot = w ? 11 : 7;
    mbar_wait(EMPTY + 8 * stslot, 0);
    {
        float2 pw = q == 0 ? make_float2(1.f, 0.f) : (q == 1 ? l32 : (q == 2 ? l64 : cmul(l64, l32)));
        float2 h = cfma(pw, part, cq);
        const uint32_t hp = sb + stslot * SL + (2 * ww) * 2048 + g * 16 + q * 4;
#pragma unroll
        for (int j = 0; j < 16; j++) {
            float2 h0 = cfma(lam, h, make_float2(acc[4 * j], acc[4 * j + 2]));
            h = cfma(lam, h0, make_float2(acc[4 * j + 1], acc[4 * j + 3]));
            sts32(hp + j * 128, pack_bf16(h0.x, h.x));
            sts32(hp + 2048 + j * 128, pack_bf16(h0.y, h.y));
        }
    }
    fence_async_smem();
    bar_sync(2 + w, 128);
    if (tid == 0) TS(kid, 7);
    if (elect) mbar_arrive(FULL + 8 * stslot);
    if (tid == 0) TS(kid, 8);
    wg_wait<0>();
    reg_fence(acc2);
    {
        const float one = LAYER == 1 ? 1.f : 0.f, d0 = LAYER == 1 ? D0 : 1.f, d1 = LAYER == 1 ? D1 : 1.f;
#pragma unroll
        for (int j = 0; j < 16; j++) {
            float2 r = *reinterpret_cast<const float2*>(s_rs + 8 * j + 2 * q);
            acc2[4 * j] *= fmaf(r.x, d0, one); acc2[4 * j + 1] *= fmaf(r.y, d0, one);
            acc2[4 * j + 2] *= fmaf(r.x, d1, one); acc2[4 * j + 3] *= fmaf(r.y, d1, one);
        }
        if (LAYER == 0 && (kt >> 1) == hf) {
            const int sx = 2 * (kt & 1) + w;
            const uint32_t xa = sb + (sx == 0 ? 12 : 7 + sx) * SL + (2 * ww) * 2048 + g * 16 + q * 4;
#pragma unroll
            for (int j = 0; j < 16; j++) {
                uint32_t u0, u1;
                asm volatile("ld.shared.u32 %0, [%1];" : "=r"(u0) : "r"(xa + j * 128));
                asm volatile("ld.shared.u32 %0, [%1];" : "=r"(u1) : "r"(xa + 2048 + j * 128));
                acc2[4 * j] += bf_lo(u0); acc2[4 * j + 1] += bf_hi(u0); acc2[4 * j + 2] += bf_lo(u1); acc2[4 * j + 3] += bf_hi(u1);
            }
        }
    }
    if (tid == 0) TS(kid, 20);
    bar_sync(2 + w, 128);
    if (elect) mbar_arrive(XDONE);
    if (tid == 0) TS(kid, 21);
    asm volatile("" : "+r"(sb));
#pragma unroll
    for (int s = 0; s < 8; s++) {
        const int as = s < 3 ? 4 + s : (s < 5 ? s - 3 : (s == 5 ? 4 : (s == 6 ? 5 : 7)));
        const int hs = s == 0 ? 7 : (s == 1 ? 11 : (s < 4 ? s : (s == 4 ? 12 : s + 3)));
        mbar_wait(FULL + 8 * as, s < 3 ? 1 : 0);
        mbar_wait(FULL + 8 * hs, (s < 2 || s == 4) ? 1 : 0);
        if (tid == 0) TS(kid, 9 + s);
        wg_fence();
#pragma unroll
        for (int kk = 0; kk < 4; kk++)
            mma128_ss<1>(acc2, mkdesc(sb + as * SL + w * 1024 + kk * 4096, 2048, 128), mkdesc(sb + hs * SL + kk * 4096, 2048, 128), 1);
        wg_commit();
        if (s > 0 && s <= 3) {
            wg_wait<1>();
            if (elect) {
                if (s <= 2) mbar_arrive(HS0 + 8 * (s - 1));
                else { mbar_wait(KB + 8 * K_PUB, 0); mbar_arrive_remote(mapa(PRDY, 1 - hf)); }
            }
        }
    }
    wg_wait<0>();
    reg_fence(acc2);
    if (tid == 0) TS(kid, 17);
    float v[32];
    exchange(acc2, v, hf, tid, sb + (w ? 6 : 11) * SL, PRDY, PDAT + 8 * w, LAYER == 1);
    if (tid == 0) TS(kid, 18);
    if (LAYER == 0) {
        bar_sync(1, 256);
        finalize_freq(v, kt, tt, hf, sb + 2 * SL, sred, tid, g_SSQ + 2048, 2, sb + OFF_BAR + 8 * (B_DONE + 2), live);
    } else {
        const float Dd = hf ? D1 : D0;
        const float* s_mean = reinterpret_cast<const float*>(sm + OFF_MEAN);
        float* op = P.out + (size_t)(tt * 128 + q * 32) * 512 + m0 + 8 * hf;
#pragma unroll
        for (int j = 0; j < 16; j++) {
            float2 r = *reinterpret_cast<const float2*>(s_rs + 8 * j + 2 * q), m = *reinterpret_cast<const float2*>(s_mean + 8 * j + 2 * q);
            if (live) {
                op[(size_t)(2 * j) * 512] = v[2 * j] - m.x * r.x * Dd;
                op[(size_t)(2 * j + 1) * 512] = v[2 * j + 1] - m.y * r.y * Dd;
            }
        }
    }
    if (tid == 0) { TS(kid, 19); TSG(kid, 31); }
}

__global__ void __cluster_dims__(2, 1, 1) __launch_bounds__(384, 1) mega_kernel(const Params P, const __grid_constant__ Maps M) {
    extern __shared__ __align__(1024) unsigned char sm[];
    const int tid = threadIdx.x, b = blockIdx.x & 127;
    const bool live = blockIdx.x < 128, scout0 = blockIdx.x >= 130;
    const uint32_t sb = smem_u32(sm), BAR = sb + OFF_BAR;
    const int tt = b >> 3, pt = b & 7, kt = pt >> 1, hf = pt & 1;
    if (tid == 256) { TS(0, 0); TSG(0, 30); TS(7, 0); TSG(7, 30); TSG(7, 31); }
    if (tid == 351) {
        for (int i = 0; i < 4; i++) mbar_init(BAR + 8 * (B_T1 + i), 1);
        asm volatile("fence.mbarrier_init.release.cluster;" ::: "memory");
        if (live) {
            mbar_expect(BAR + 8 * B_T1, 32768);
            tma4d(sb + 8 * SL, &M.x, hf * 256, 0, 4 * tt, 0, BAR + 8 * B_T1);
            bulk_g2s(sb, g_T1.v + (kt * 8 + 4 * hf) * 8192, 16384, BAR + 8 * B_T1);
        }
    }
    __syncwarp();
    {
        const int i = (tid & 31) * 12 + (tid >> 5);
        if ((tid & 31) < 9 && i < NBAR && i >= B_T1 + 4) {
            int cnt = 1, tx = 0;
            if (i == B_PRDY0 || i == B_BDEAD) cnt = 2;
            if (i == B_BOUT) cnt = 32;
            if (i >= B_KS) { const int k = (i - B_KS) % K_N; cnt = (k < 13 || k >= K_PDAT) ? 1 : 2; }
            mbar_init(BAR + 8 * i, cnt);
            if (i == B_OPB || i == B_OPC) tx = 32768;
            else if (i == B_WRAW) tx = 2 * 8224;
            else if (i == B_PDAT0 || i == B_PDAT0 + 1) tx = 8192;
            else if (i == B_PDATW) tx = 8192;
            else if (i == B_PDATB || i == B_PDATB + 1) tx = 8192;
            else if (i >= B_KS && (i - B_KS) % K_N >= K_PDAT) tx = (i >= B_KS + K_N) ? 16384 : 8192;
            else if (i == B_XFF || i == B_XFF + 1) tx = 16384 + 8192;
            if (tx) mbar_expect(BAR + 8 * i, tx);
        }
        asm volatile("fence.mbarrier_init.release.cluster;" ::: "memory");
    }
    static_assert(NBAR <= 108, "barrier init map");
    if (tid == 256) TS(0, 16);
    const unsigned epoch = *reinterpret_cast<volatile unsigned*>(&g_epoch) + 1;
    const unsigned target = epoch * 128u;
    __syncthreads();
    if (tid == 256) TS(0, 17);
    asm volatile("barrier.cluster.arrive.relaxed.aligned;" ::: "memory");

    const int wgi = __shfl_sync(0xffffffffu, tid >> 7, 0);
    if (wgi == 2) {
        asm volatile("setmaxnreg.dec.sync.aligned.u32 104;");
        const int aw = __shfl_sync(0xffffffffu, (tid >> 5) - 8, 0), lane = tid & 31;
        auto kc = [&](int s) { return s < 4 ? 4 * (1 - hf) + ((s + kt) & 3) : 4 * hf + (s - 4); };
        auto pcs = [&](int s) { return s < 2 ? 2 * pt + s : 2 * (hf + 2 * ((kt + 1 + ((s - 2) >> 1)) & 3)) + (s & 1); };
        if (live || scout0) p0_aux(P, M, sm, sb, tid - 256, b, target, live);
        if (scout0) return;
        {
            if (aw == 0) { if (lane == 0) {
#pragma unroll 1
                for (int L = 0; L < 2; L++) {
                    const uint32_t KB = BAR + 8 * (B_KS + L * K_N), FULL = KB, EMPTY = KB + 8 * K_EMPTY;
                    auto ld = [&](int slot, uint32_t waitbar, const uint16_t* src) {
                        if (waitbar) mbar_wait(waitbar, 0);
                        mbar_expect(FULL + 8 * slot, 16384);
                        bulk_g2s(sb + slot * SL, src, 16384, FULL + 8 * slot);
                    };
                    const uint16_t* WB = g_WB + (size_t)pt * 8 * 8192;
                    if (live || L == 1) mbar_wait(BAR + 8 * (B_DONE + 2 * L), 0);
                    if (L == 0) {
                        if (live) mbar_wait(BAR + 8 * B_BDEAD, 0);
                        gb_wait(4, target, live);
                        if (b == 0 && live) g_epoch = epoch;
                    } else {
                        mbar_wait(BAR + 8 * (B_XFF + 1), 0);
                    }
                    for (int s = (L == 0 && live) ? 6 : 0; s < 8; s++) ld(s, (L == 0 && s == 7 && live) ? BAR + 8 * B_AUXD : 0, WB + kc(s) * 8192);
                    const uint16_t* WE = (L == 0 ? g_WE1 : g_T2.v) + (size_t)(kt * 8 + 4 * hf) * 8192;
                    const uint16_t* WC = (L == 0 ? g_WC1 : g_WC2) + (size_t)(kt * 16) * 8192;
                    const uint16_t* X = g_XB + (size_t)tt * 8 * 8192;
                    mbar_wait(BAR + 8 * (B_DONE + 2 * L + 1), 0);
                    gb_wait(2 * L + 1, target, live);
                    TS(5 + L, 13);
                    for (int s = 0; s < 5; s++) ld(8 + s, 0, X + kc(s) * 8192);
                    if (L == 0) gb_wait(7, target, live);
                    for (int s = 0; s < 3; s++) {
                        if (s == 0) mbar_wait(KB + 8 * K_SDONE, 0);
                        ld(8 + s, EMPTY + 8 * (8 + s), X + kc(5 + s) * 8192);
                        ld(s, EMPTY + 8 * s, WE + s * 8192);
                    }
                    ld(3, EMPTY + 8 * 3, WE + 3 * 8192);
                    TS(5 + L, 17);
                    for (int s = 0; s < 3; s++) ld(4 + s, EMPTY + 8 * (4 + s), WC + pcs(s) * 8192);
                    if (L == 0) gb_wait(5, target, live);
                    ld(0, KB + 8 * K_XDONE, WC + pcs(3) * 8192);
                    ld(1, 0, WC + pcs(4) * 8192);
                    ld(4, KB + 8 * K_HS0, WC + pcs(5) * 8192);
                    ld(7, KB + 8 * K_PUB, WC + pcs(7) * 8192);
                    ld(5, KB + 8 * K_HS1, WC + pcs(6) * 8192);
                }
            } } else
            if (aw == 3) {
#pragma unroll 1
                for (int L = 0; L < 2; L++) {
                    const uint32_t KB = BAR + 8 * (B_KS + L * K_N), FULL = KB;
                    mbar_wait(KB + 8 * K_XDONE, 0);
                    {
                        const int s = 2 + (lane < 6 ? lane : 5);
                        const unsigned* fl = g_HFLAG + (L * 16 + tt) * 16 + pcs(s);
                        unsigned done = 0; int n = 0;
                        while (done != 63u) {
                            unsigned v;
                            asm volatile("ld.acquire.gpu.global.u32 %0, [%1];" : "=r"(v) : "l"(fl) : "memory");
                            unsigned rdy = __ballot_sync(0xffffffffu, v == epoch || !live) & 63u & ~done;
                            done |= rdy;
                            if (lane == 0) {
                                while (rdy) {
                                    const int sn = __ffs(rdy) + 1, hs = sn < 4 ? sn : (sn == 4 ? 12 : sn + 3);
                                    rdy &= rdy - 1;
                                    TS(2 + L, 20 + sn);
                                    mbar_expect(FULL + 8 * hs, 16384);
                                    bulk_g2s(sb + hs * SL, g_H + (size_t)(tt * 16 + pcs(sn)) * 8192, 16384, FULL + 8 * hs);
                                }
                            }
                            __syncwarp();
                            if (++n > (1 << 22)) break;
                        }
                    }
                    __syncwarp();
                }
            } else {
                const int kr = lane & 7, sw = aw - 1;
                float* s_rs = reinterpret_cast<float*>(sm + OFF_RS);
#pragma unroll 1
                for (int L = 0; L < 2; L++) {
                    const uint32_t KB = BAR + 8 * (B_KS + L * K_N);
                    uint4* pst = g_PST + (size_t)((L * 16 + tt) * 8) * 64;
                    mbar_wait(KB + 8 * (K_FULL + 8), 0);
                    const bool dcchunk = kc(0) == 0;
                    float a[16];
#pragma unroll
                    for (int i = 0; i < 16; i++) a[i] = 0.f;
#pragma unroll
                    for (int k8 = 0; k8 < 8; k8++) {
#pragma unroll
                        for (int i = 0; i < 2; i++) {
                            const int n8 = sw * 8 + (lane >> 3) + 4 * i;
                            uint4 v = *reinterpret_cast<const uint4*>(sm + 8 * SL + (k8 * 16 + n8) * 128 + kr * 16);
                            if (k8 == 0 && dcchunk && kr == 1) v = make_uint4(0, 0, 0, 0);
                            float f;
                            f = bf_lo(v.x); a[8 * i + 0] = fmaf(f, f, a[8 * i + 0]); f = bf_hi(v.x); a[8 * i + 1] = fmaf(f, f, a[8 * i + 1]);
                            f = bf_lo(v.y); a[8 * i + 2] = fmaf(f, f, a[8 * i + 2]); f = bf_hi(v.y); a[8 * i + 3] = fmaf(f, f, a[8 * i + 3]);
                            f = bf_lo(v.z); a[8 * i + 4] = fmaf(f, f, a[8 * i + 4]); f = bf_hi(v.z); a[8 * i + 5] = fmaf(f, f, a[8 * i + 5]);
                            f = bf_lo(v.w); a[8 * i + 6] = fmaf(f, f, a[8 * i + 6]); f = bf_hi(v.w); a[8 * i + 7] = fmaf(f, f, a[8 * i + 7]);
                        }
                    }
                    __syncwarp();
                    if (lane == 0) mbar_arrive(KB + 8 * K_SDONE);
#pragma unroll
                    for (int i = 0; i < 16; i++) {
                        a[i] += __shfl_xor_sync(0xffffffffu, a[i], 1);
                        a[i] += __shfl_xor_sync(0xffffffffu, a[i], 2);
                        a[i] += __shfl_xor_sync(0xffffffffu, a[i], 4);
                    }
                    {
                        const int i = kr >> 2, pr = kr & 3;
                        float v0 = 0.f, v1 = 0.f;
#pragma unroll
                        for (int z = 0; z < 8; z++) if (z == kr) { v0 = a[2 * z]; v1 = a[2 * z + 1]; }
                        const int n8 = sw * 8 + (lane >> 3) + 4 * i;
                        if (live) asm volatile("st.relaxed.gpu.global.v4.u32 [%0], {%1,%2,%3,%4};" ::"l"(pst + pt * 64 + n8 * 4 + pr), "r"(__float_as_uint(v0)), "r"(epoch), "r"(__float_as_uint(v1)), "r"(epoch) : "memory");
                    }
                    if (L == 1 && b < 32 && live) { g_SSQ[b * 64 + sw * 32 + lane] = 0.f; }
                    if (L == 1 && sw == 1 && lane < 16) {
                        uint4 dv = __ldcg(reinterpret_cast<const uint4*>(g_XB + (size_t)tt * 8 * 8192 + lane * 64 + 8));
                        const float c = 0.044194173824159220275f;
                        sts128(sb + OFF_MEAN + lane * 32, bf_lo(dv.x) * c, bf_hi(dv.x) * c, bf_lo(dv.y) * c, bf_hi(dv.y) * c);
                        sts128(sb + OFF_MEAN + lane * 32 + 16, bf_lo(dv.z) * c, bf_hi(dv.z) * c, bf_lo(dv.w) * c, bf_hi(dv.w) * c);
                    }
                    const int pi = sw * 32 + lane;
                    uint4 r[8];
                    int n = live ? 0 : (1 << 22); bool ok;
                    do {
                        ok = true;
#pragma unroll
                        for (int i = 0; i < 8; i++) {
                            asm volatile("ld.relaxed.gpu.global.v4.u32 {%0,%1,%2,%3}, [%4];" : "=r"(r[i].x), "=r"(r[i].y), "=r"(r[i].z), "=r"(r[i].w) : "l"(pst + i * 64 + pi) : "memory");
                            ok = ok && r[i].y == epoch && r[i].w == epoch;
                        }
                        if (++n > (1 << 22)) break;
                    } while (!ok);
                    float s0 = 0.f, s1 = 0.f;
#pragma unroll
                    for (int i = 0; i < 8; i++) { s0 += __uint_as_float(r[i].x); s1 += __uint_as_float(r[i].z); }
                    *reinterpret_cast<float2*>(s_rs + 2 * pi) = make_float2(rsqrtf(s0 * (1.f / 512.f) + 1e-5f), rsqrtf(s1 * (1.f / 512.f) + 1e-5f));
                    __syncwarp();
                    if (lane == 0) {
                        mbar_arrive(KB + 8 * K_RSBAR);
                        const int stslot = sw ? 11 : 7;
                        mbar_wait(KB + 8 * (K_FULL + stslot), 0);
                        mbar_wait(KB + 8 * (K_FULL + stslot), 1);
                        if (live) bulk_s2g(g_H + (size_t)(tt * 16 + 2 * pt + sw) * 8192, sb + stslot * SL, 16384);
                        bulk_commit();
                        bulk_wait_all();
                        if (live) asm volatile("st.release.gpu.global.u32 [%0], %1;" ::"l"(g_HFLAG + (L * 16 + tt) * 16 + 2 * pt + sw), "r"(epoch) : "memory");
                        mbar_arrive(KB + 8 * K_PUB);
                    }
                    __syncwarp();
                }
            }
        }
    } else {
        if (tid == 0) TS(0, 18);
        asm volatile("setmaxnreg.inc.sync.aligned.u32 200;");
        if (live || scout0) p0_compute(P, M, sm, sb, tid, b, target, live);
        else asm volatile("barrier.cluster.wait.aligned;" ::: "memory");
        if (scout0) return;
        float2 lam, coef;
        {
            const int ch = pt * 64 + (tid >> 5) * 8 + ((tid & 31) >> 2);
            const float lr = __bfloat162float(P.Lre[ch]), li = __bfloat162float(P.Lim[ch]);
            float dt = __bfloat162float(__float2bfloat16_rn(expf(__bfloat162float(P.logdt[ch]))));
            float er = expf(dt * lr), sn, cs;
            sincospif(dt * li * 0.31830988618379067f, &sn, &cs);
            lam = make_float2(er * cs, er * sn);
            float inv = 1.f / (lr * lr + li * li), nr = lam.x - 1.f, ni = lam.y;
            coef = make_float2((nr * lr + ni * li) * inv, (ni * lr - nr * li) * inv);
        }
#pragma unroll 1
        for (int L = 0; L < 2; L++) {
            kc_compute(M, sm, sb, tid, b, L, target, live);
            ks_compute(P, M, sm, sb, tid, b, L, epoch, lam, coef, live);
        }
    }
}

extern "C" void kernel_launch(void* const* d_in, const int* in_sizes, int n_in, void* d_out, int out_size) {
    (void)in_sizes; (void)n_in; (void)out_size;
    typedef CUresult (*EncFn)(CUtensorMap*, CUtensorMapDataType, cuuint32_t, void*, const cuuint64_t*, const cuuint64_t*, const cuuint32_t*, const cuuint32_t*,
                              CUtensorMapInterleave, CUtensorMapSwizzle, CUtensorMapL2promotion, CUtensorMapFloatOOBfill);
    static EncFn enc = nullptr;
    static int grid = 128;
    if (!enc) {
        cudaFuncSetAttribute(mega_kernel, cudaFuncAttributeMaxDynamicSharedMemorySize, MK_SMEM);
        void* fn = nullptr; cudaDriverEntryPointQueryResult qr;
        cudaGetDriverEntryPoint("cuTensorMapEncodeTiled", &fn, cudaEnableDefault, &qr);
        enc = (EncFn)fn;
        cudaLaunchConfig_t cfg = {}; cfg.gridDim = dim3(132); cfg.blockDim = dim3(384); cfg.dynamicSmemBytes = MK_SMEM;
        cudaLaunchAttribute at[1]; at[0].id = cudaLaunchAttributeClusterDimension; at[0].val.clusterDim.x = 2; at[0].val.clusterDim.y = 1; at[0].val.clusterDim.z = 1;
        cfg.attrs = at; cfg.numAttrs = 1;
        int nc = 0;
        if (cudaOccupancyMaxActiveClusters(&nc, mega_kernel, &cfg) == cudaSuccess) grid = nc >= 66 ? 132 : (nc >= 65 ? 130 : 128);
        (void)cudaGetLastError();
    }
    Maps M;
    {
        const cuuint32_t es[4] = {1, 1, 1, 1};
        {
            const cuuint64_t dim[4] = {512, 2, 64, 16}; const cuuint64_t st[3] = {1024, 32 * 1024, 2 * 1024}; const cuuint32_t box[4] = {64, 2, 4, 16};
            enc(&M.x, CU_TENSOR_MAP_DATA_TYPE_BFLOAT16, 4, d_in[0], dim, st, box, es, CU_TENSOR_MAP_INTERLEAVE_NONE, CU_TENSOR_MAP_SWIZZLE_128B, CU_TENSOR_MAP_L2_PROMOTION_NONE, CU_TENSOR_MAP_FLOAT_OOB_FILL_NONE);
        }
        {
            const cuuint32_t es5[5] = {1, 1, 1, 1, 1};
            void *pxb = nullptr, *pwf = nullptr;
            cudaGetSymbolAddress(&pxb, g_XB); cudaGetSymbolAddress(&pwf, g_WF);
            { const cuuint64_t dim[5] = {32, 16, 16, 2, 64}; const cuuint64_t st[4] = {128, 131072, 64, 2048}; const cuuint32_t box[5] = {32, 16, 16, 1, 1};
              enc(&M.xb, CU_TENSOR_MAP_DATA_TYPE_BFLOAT16, 5, pxb, dim, st, box, es5, CU_TENSOR_MAP_INTERLEAVE_NONE, CU_TENSOR_MAP_SWIZZLE_NONE, CU_TENSOR_MAP_L2_PROMOTION_NONE, CU_TENSOR_MAP_FLOAT_OOB_FILL_NONE); }
            { const cuuint64_t dim[3] = {16, 128, 256}; const cuuint64_t st[2] = {64, 8192}; const cuuint32_t box[3] = {16, 1, 256};
              enc(&M.wf, CU_TENSOR_MAP_DATA_TYPE_UINT32, 3, pwf, dim, st, box, es5, CU_TENSOR_MAP_INTERLEAVE_NONE, CU_TENSOR_MAP_SWIZZLE_NONE, CU_TENSOR_MAP_L2_PROMOTION_NONE, CU_TENSOR_MAP_FLOAT_OOB_FILL_NONE); }
        }
        const cuuint64_t dim[2] = {512, 512}; const cuuint64_t st[1] = {1024};
        const cuuint32_t boxb[2] = {64, 32}, boxc[2] = {64, 64};
        enc(&M.bre, CU_TENSOR_MAP_DATA_TYPE_BFLOAT16, 2, d_in[6], dim, st, boxb, es, CU_TENSOR_MAP_INTERLEAVE_NONE, CU_TENSOR_MAP_SWIZZLE_128B, CU_TENSOR_MAP_L2_PROMOTION_NONE, CU_TENSOR_MAP_FLOAT_OOB_FILL_NONE);
        enc(&M.bim, CU_TENSOR_MAP_DATA_TYPE_BFLOAT16, 2, d_in[7], dim, st, boxb, es, CU_TENSOR_MAP_INTERLEAVE_NONE, CU_TENSOR_MAP_SWIZZLE_128B, CU_TENSOR_MAP_L2_PROMOTION_NONE, CU_TENSOR_MAP_FLOAT_OOB_FILL_NONE);
        enc(&M.cre, CU_TENSOR_MAP_DATA_TYPE_BFLOAT16, 2, d_in[8], dim, st, boxc, es, CU_TENSOR_MAP_INTERLEAVE_NONE, CU_TENSOR_MAP_SWIZZLE_128B, CU_TENSOR_MAP_L2_PROMOTION_NONE, CU_TENSOR_MAP_FLOAT_OOB_FILL_NONE);
        enc(&M.cim, CU_TENSOR_MAP_DATA_TYPE_BFLOAT16, 2, d_in[9], dim, st, boxc, es, CU_TENSOR_MAP_INTERLEAVE_NONE, CU_TENSOR_MAP_SWIZZLE_128B, CU_TENSOR_MAP_L2_PROMOTION_NONE, CU_TENSOR_MAP_FLOAT_OOB_FILL_NONE);
    }
    Params P;
    P.x = (const uint16_t*)d_in[0]; P.wr = (const uint16_t*)d_in[1]; P.wi = (const uint16_t*)d_in[2];
    P.Lre = (const __nv_bfloat16*)d_in[4]; P.Lim = (const __nv_bfloat16*)d_in[5];
    P.Bre = (const uint16_t*)d_in[6]; P.Bim = (const uint16_t*)d_in[7]; P.Cre = (const uint16_t*)d_in[8]; P.Cim = (const uint16_t*)d_in[9];
    P.logdt = (const __nv_bfloat16*)d_in[10]; P.Dsk = (const __nv_bfloat16*)d_in[11]; P.Dsk16 = (const uint16_t*)d_in[11];
    P.out = (float*)d_out;
    mega_kernel<<<grid, 384, MK_SMEM>>>(P, M);
}
```
